```python
import torch

def _softmax(x, axis=-1):
    return torch.softmax(x, dim=axis)
def _gelu(x):
    return torch.nn.functional.gelu(x, approximate="tanh")
def _silu(x):
    return torch.nn.functional.silu(x)
def _sigmoid(x):
    return torch.sigmoid(x)
def _layernorm(x, axis=-1, eps=1e-5):
    m = x.mean(dim=axis, keepdim=True)
    v = x.var(dim=axis, keepdim=True, unbiased=False)
    return (x - m) / torch.sqrt(v + eps)
def _scatter_add(tgt, idx, src, axis=0):
    return tgt.clone().index_add_(axis, idx, src)
def _segment_sum(src, seg, n):
    out = torch.zeros((n,) + src.shape[1:], dtype=src.dtype)
    return out.index_add_(0, seg, src)
def _pad(x, pw):
    flat = tuple(v for pair in reversed(pw) for v in pair)
    return torch.nn.functional.pad(x, flat)

kernel_name = 'gated_mix__softmax_full_mha__moe_arch_mod__prompt'

def setup_inputs():

    _w = (lambda a: (lambda t: t.to(torch.bfloat16) if t.is_floating_point() else t)(torch.as_tensor(a)))
    def _A_setup():
        B, S, D = 1, 2048, 512
        return {
            "x": _w((lambda *s: torch.randn(*s, dtype=torch.bfloat16) * 0.05)(B, S, D)),
            "wqkv": _w((lambda *s: torch.randn(*s, dtype=torch.bfloat16) * 0.8)(D, 3 * D)),
            "wo": _w((lambda *s: torch.randn(*s, dtype=torch.bfloat16) * 0.1)(D, D)),
        }
    _A_in = _A_setup()

    def _B_setup():
        B, S, D, F, C = 1, 2048, 512, 1792, 2
        return {
            "x": _w((lambda *s: torch.randn(*s, dtype=torch.bfloat16) * 0.05)(B, S, D)),
            "w_r": _w((lambda *s: torch.randn(*s, dtype=torch.bfloat16) * 1.6)(D)),
            "w_gate": _w((lambda *s: torch.randn(*s, dtype=torch.bfloat16) * 0.2)(D, F)),
            "w_up": _w((lambda *s: torch.randn(*s, dtype=torch.bfloat16) * 0.2)(D, F)),
            "w_down": _w((lambda *s: torch.randn(*s, dtype=torch.bfloat16) * 0.2)(F, D)),
        }
    _B_in = _B_setup()

    return {
        "A_x": _A_in["x"],
        "A_wqkv": _A_in["wqkv"],
        "A_wo": _A_in["wo"],
        "B_x": _B_in["x"],
        "B_w_r": _B_in["w_r"],
        "B_w_gate": _B_in["w_gate"],
        "B_w_up": _B_in["w_up"],
        "B_w_down": _B_in["w_down"],
        "gate_w": _w((lambda *s: torch.randn(*s, dtype=torch.bfloat16) * 0.05)(512) * 16.0),
    }

def reference(A_x, A_wqkv, A_wo, B_x, B_w_r, B_w_gate, B_w_up, B_w_down, gate_w):
    def _A_ref(x, wqkv, wo):
        B, S, D = x.shape
        H = 32; Dh = D // H
        qkv = (lambda x, *d: x.permute(*d))((x @ wqkv).reshape(B, S, 3, H, Dh), 2, 0, 3, 1, 4)
        q, k, v = qkv[0], qkv[1], qkv[2]
        scale = Dh ** -0.5
        scores = torch.einsum("bhqd,bhkd->bhqk", q, k) * scale
        p = _softmax(scores, axis=-1)
        o = torch.einsum("bhqk,bhkd->bhqd", p, v)
        return (lambda x, *d: x.permute(*d))(o, 0, 2, 1, 3).reshape(B, S, D) @ wo

    def _B_ref(x, w_r, w_gate, w_up, w_down):
        B, S, D = x.shape
        C = 2
        r = x @ w_r
        idx = torch.argsort(-r, axis=-1)[:, :C]
        idx_e = (lambda x, n, axis: torch.repeat_interleave(x, n, dim=axis))(idx.reshape(B, C, 1), D, axis=2)
        x_sel = (lambda x, i, axis: torch.take_along_dim(x, i, dim=axis))(x, idx_e, axis=1)
        g = _silu(x_sel @ w_gate)
        u = x_sel @ w_up
        y = (g * u) @ w_down
        r_sel = _sigmoid((lambda x, i, axis: torch.take_along_dim(x, i, dim=axis))(r, idx, axis=1))
        y = y * r_sel.reshape(B, C, 1)
        b_off = (torch.arange(B) * S).reshape(B, 1)
        flat_idx = (idx + b_off).reshape(B * C)
        zero = (x * 0.0).reshape(B * S, D)
        upd = _scatter_add(zero, flat_idx, y.reshape(B * C, D), axis=0)
        return x + upd.reshape(B, S, D)

    x = A_x
    g = _sigmoid((x * gate_w).sum(-1, keepdims=True))
    a = _A_ref(x, A_wqkv, A_wo)
    b = _B_ref(x, B_w_r, B_w_gate, B_w_up, B_w_down)
    return g * a + (1 - g) * b
```

```cpp
#include <cuda_runtime.h>
#include <cuda.h>
#include <cuda_bf16.h>
#include <cuda_fp16.h>
#include <stdint.h>

typedef __nv_bfloat16 bf16;

constexpr int SEQ = 2048, DM = 512, NH = 32, FF = 1792;
constexpr int NMAIN = 128, NFFN = 4, NCTA = NMAIN + NFFN, NTHR = 512;
constexpr int FSL = FF / NFFN;
#define NMU 10

constexpr int NSTAGE = 5, STG_A = 16384, STG_B = 24576, STG = STG_A + STG_B;
constexpr int SM_K = 0, SM_V0 = 65536, SM_ONE = 98304, SM_V1 = 98560;
constexpr int SM_Q = 132096, SM_WO0 = 148480;
constexpr int SM_A = 0, SM_WO1 = 65536, SM_OUT = SM_Q;
constexpr int SM_BAR = 214016;
constexpr int SM_TOTAL = SM_BAR + 512 + 1024;
constexpr int B_FULL = 0, B_EMPTY = 5, B_KV = 8, B_Q = 24, B_WO0 = 25, B_WO1 = 26, B_A = 27, B_N = 31;

__device__ uint4 g_q[NH * 4096];
__device__ uint4 g_k[NH * 4096];
__device__ uint4 g_v0[NH * 2048];
__device__ uint4 g_v1[NH * 2048];
__device__ uint4 g_o[32 * NH * 128];
__device__ uint2 g_stat[NH * 128];
__device__ uint2 g_r[SEQ], g_g[SEQ];
__device__ float g_y[NFFN * 2 * DM];
__device__ uint2 g_fy[NFFN];
__device__ uint32_t g_f1[8 * 32];
__device__ uint32_t g_f2[32 * NH];
__device__ uint32_t g_epoch[NCTA];
__device__ float g_slow[NH * SEQ * 32];
#define TSTAMP(i, cond)

struct Params {
  const bf16 *x, *wqkv, *wr, *wg, *wu, *wd, *gw;
};

constexpr uint32_t SPIN_LIMIT = 1u << 22;
constexpr long long WAIT_LIMIT = 1ll << 32;
__device__ __forceinline__ void wg_fence() { asm volatile("wgmma.fence.sync.aligned;" ::: "memory"); }
__device__ __forceinline__ void wg_commit() { asm volatile("wgmma.commit_group.sync.aligned;" ::: "memory"); }
template <int N> __device__ __forceinline__ void wg_wait() { asm volatile("wgmma.wait_group.sync.aligned %0;" ::"n"(N) : "memory"); }
template <int N> __device__ __forceinline__ void pin(uint32_t* s) {
#pragma unroll
  for (int i = 0; i < N; i++) asm volatile("" : "+r"(s[i])::"memory");
}
template <int N> __device__ __forceinline__ void pin(float* s) {
#pragma unroll
  for (int i = 0; i < N; i++) asm volatile("" : "+f"(s[i])::"memory");
}
__device__ __forceinline__ void mbar_init(uint32_t bar, uint32_t cnt) { asm volatile("mbarrier.init.shared::cta.b64 [%0], %1;" ::"r"(bar), "r"(cnt) : "memory"); }
__device__ __forceinline__ void mbar_expect(uint32_t bar, uint32_t bytes) { asm volatile("mbarrier.arrive.expect_tx.shared::cta.b64 _, [%0], %1;" ::"r"(bar), "r"(bytes) : "memory"); }
__device__ __forceinline__ void mbar_arrive(uint32_t bar) { asm volatile("mbarrier.arrive.shared::cta.b64 _, [%0];" ::"r"(bar) : "memory"); }
__device__ __forceinline__ void mbar_wait(uint32_t bar, uint32_t parity) {
  asm volatile("{.reg .pred p; .reg .b64 t0, t1;\n"
    "mbarrier.try_wait.parity.shared::cta.b64 p, [%0], %1;\n"
    "@p bra D;\n"
    "mov.u64 t0, %clock64;\n"
    "W: mbarrier.try_wait.parity.shared::cta.b64 p, [%0], %1;\n"
    "@p bra D;\n"
    "mov.u64 t1, %clock64; sub.u64 t1, t1, t0; setp.lt.u64 p, t1, %2;\n"
    "@p bra W;\n"
    "trap;\n"
    "D:}" ::"r"(bar), "r"(parity), "n"(WAIT_LIMIT) : "memory");
}
__device__ __forceinline__ void tma2d(uint32_t dst, const CUtensorMap* m, int c0, int c1, uint32_t bar) {
  asm volatile("cp.async.bulk.tensor.2d.shared::cluster.global.mbarrier::complete_tx::bytes [%0], [%1, {%3, %4}], [%2];"
    ::"r"(dst), "l"(m), "r"(bar), "r"(c0), "r"(c1) : "memory");
}
__device__ __forceinline__ void bulk(uint32_t dst, const void* src, uint32_t bytes, uint32_t bar) {
  asm volatile("cp.async.bulk.shared::cluster.global.mbarrier::complete_tx::bytes [%0], [%1], %2, [%3];"
    ::"r"(dst), "l"(src), "r"(bytes), "r"(bar) : "memory");
}
__device__ __forceinline__ void fence_async() { asm volatile("fence.proxy.async;" ::: "memory"); }
__device__ __forceinline__ void bar_sync(int id, int n) { asm volatile("bar.sync %0, %1;" ::"r"(id), "r"(n) : "memory"); }
__device__ __forceinline__ void bar_arrive(int id, int n) { asm volatile("bar.arrive %0, %1;" ::"r"(id), "r"(n) : "memory"); }
__device__ __forceinline__ bool bar_or(int id, int n, bool v) {
  uint32_t r;
  asm volatile("{.reg .pred p, q; setp.ne.b32 q, %3, 0; bar.red.or.pred p, %1, %2, q; selp.b32 %0, 1, 0, p;}" : "=r"(r) : "r"(id), "r"(n), "r"((uint32_t)v) : "memory");
  return r != 0;
}
__device__ __forceinline__ void flag_set(uint32_t* f, uint32_t e) {
  fence_async();
  asm volatile("st.release.gpu.global.u32 [%0], %1;" ::"l"(f), "r"(e) : "memory");
}
__device__ __forceinline__ void flag_wait(const uint32_t* f, uint32_t e) {
  uint32_t v, c = 0;
  do {
    asm volatile("ld.acquire.gpu.global.u32 %0, [%1];" : "=r"(v) : "l"(f) : "memory");
    if (++c > SPIN_LIMIT) __trap();
  } while (v != e);
}
__device__ __forceinline__ void cell_set(uint2* p, uint32_t v, uint32_t e) { asm volatile("st.relaxed.gpu.global.v2.u32 [%0], {%1, %2};" ::"l"(p), "r"(v), "r"(e) : "memory"); }
__device__ __forceinline__ uint32_t cell_get(const uint2* p, uint32_t e) {
  unsigned long long v; uint32_t c = 0;
  do {
    asm volatile("ld.relaxed.gpu.global.u64 %0, [%1];" : "=l"(v) : "l"(p) : "memory");
    if (++c > SPIN_LIMIT) __trap();
  } while ((uint32_t)(v >> 32) != e);
  return (uint32_t)v;
}
__device__ __forceinline__ uint64_t make_desc(uint32_t addr, uint32_t lbo, uint32_t sbo, uint32_t swz) {
  return (uint64_t)((addr & 0x3FFFF) >> 4) | ((uint64_t)(lbo >> 4) << 16) | ((uint64_t)(sbo >> 4) << 32) | ((uint64_t)swz << 62);
}
__device__ __forceinline__ uint32_t pack_h2(float lo, float hi) { uint32_t r; asm("cvt.rn.f16x2.f32 %0, %1, %2;" : "=r"(r) : "f"(hi), "f"(lo)); return r; }
__device__ __forceinline__ uint32_t pack_b2(float lo, float hi) { uint32_t r; asm("cvt.rn.bf16x2.f32 %0, %1, %2;" : "=r"(r) : "f"(hi), "f"(lo)); return r; }
__device__ __forceinline__ float b_lo(uint32_t v) { return __uint_as_float(v << 16); }
__device__ __forceinline__ float b_hi(uint32_t v) { return __uint_as_float(v & 0xffff0000u); }
__device__ __forceinline__ float h_lo(uint32_t v) { return __half2float(__ushort_as_half((unsigned short)(v & 0xffff))); }
__device__ __forceinline__ float h_hi(uint32_t v) { return __half2float(__ushort_as_half((unsigned short)(v >> 16))); }
__device__ __forceinline__ float sigmoidf(float v) { return 1.f / (1.f + __expf(-v)); }

__device__ __forceinline__ void wg_qk(uint32_t* d, const uint32_t* a, uint64_t desc) {
  asm volatile("{.reg .pred p; setp.ne.b32 p, 0, 0;\n"
    "wgmma.mma_async.sync.aligned.m64n128k16.f16.f16.f16 {%0,%1,%2,%3,%4,%5,%6,%7,%8,%9,%10,%11,%12,%13,%14,%15,%16,%17,%18,%19,%20,%21,%22,%23,%24,%25,%26,%27,%28,%29,%30,%31}, {%32,%33,%34,%35}, %36, p, 1, 1, 0;}\n"
    : "=r"(d[0]), "=r"(d[1]), "=r"(d[2]), "=r"(d[3]), "=r"(d[4]), "=r"(d[5]), "=r"(d[6]), "=r"(d[7]),
      "=r"(d[8]), "=r"(d[9]), "=r"(d[10]), "=r"(d[11]), "=r"(d[12]), "=r"(d[13]), "=r"(d[14]), "=r"(d[15]),
      "=r"(d[16]), "=r"(d[17]), "=r"(d[18]), "=r"(d[19]), "=r"(d[20]), "=r"(d[21]), "=r"(d[22]), "=r"(d[23]),
      "=r"(d[24]), "=r"(d[25]), "=r"(d[26]), "=r"(d[27]), "=r"(d[28]), "=r"(d[29]), "=r"(d[30]), "=r"(d[31])
    : "r"(a[0]), "r"(a[1]), "r"(a[2]), "r"(a[3]), "l"(desc));
}
__device__ __forceinline__ void wg_pv(float* d, const uint32_t* a, uint64_t desc) {
  asm volatile("{.reg .pred p; setp.eq.b32 p, 0, 0;\n"
    "wgmma.mma_async.sync.aligned.m64n24k16.f32.f16.f16 {%0,%1,%2,%3,%4,%5,%6,%7,%8,%9,%10,%11}, {%12,%13,%14,%15}, %16, p, 1, 1, 1;}\n"
    : "+f"(d[0]), "+f"(d[1]), "+f"(d[2]), "+f"(d[3]), "+f"(d[4]), "+f"(d[5]), "+f"(d[6]), "+f"(d[7]),
      "+f"(d[8]), "+f"(d[9]), "+f"(d[10]), "+f"(d[11])
    : "r"(a[0]), "r"(a[1]), "r"(a[2]), "r"(a[3]), "l"(desc));
}
__device__ __forceinline__ void wg_ss_n192(float* d, uint64_t da, uint64_t db, int acc) {
  asm volatile("{.reg .pred p; setp.ne.b32 p, %98, 0;\n"
    "wgmma.mma_async.sync.aligned.m64n192k16.f32.bf16.bf16 {%0,%1,%2,%3,%4,%5,%6,%7,%8,%9,%10,%11,%12,%13,%14,%15,%16,%17,%18,%19,%20,%21,%22,%23,%24,%25,%26,%27,%28,%29,%30,%31,%32,%33,%34,%35,%36,%37,%38,%39,%40,%41,%42,%43,%44,%45,%46,%47,%48,%49,%50,%51,%52,%53,%54,%55,%56,%57,%58,%59,%60,%61,%62,%63,%64,%65,%66,%67,%68,%69,%70,%71,%72,%73,%74,%75,%76,%77,%78,%79,%80,%81,%82,%83,%84,%85,%86,%87,%88,%89,%90,%91,%92,%93,%94,%95}, %96, %97, p, 1, 1, 0, 1;}\n"
    : "+f"(d[0]), "+f"(d[1]), "+f"(d[2]), "+f"(d[3]), "+f"(d[4]), "+f"(d[5]), "+f"(d[6]), "+f"(d[7]),
      "+f"(d[8]), "+f"(d[9]), "+f"(d[10]), "+f"(d[11]), "+f"(d[12]), "+f"(d[13]), "+f"(d[14]), "+f"(d[15]),
      "+f"(d[16]), "+f"(d[17]), "+f"(d[18]), "+f"(d[19]), "+f"(d[20]), "+f"(d[21]), "+f"(d[22]), "+f"(d[23]),
      "+f"(d[24]), "+f"(d[25]), "+f"(d[26]), "+f"(d[27]), "+f"(d[28]), "+f"(d[29]), "+f"(d[30]), "+f"(d[31]),
      "+f"(d[32]), "+f"(d[33]), "+f"(d[34]), "+f"(d[35]), "+f"(d[36]), "+f"(d[37]), "+f"(d[38]), "+f"(d[39]),
      "+f"(d[40]), "+f"(d[41]), "+f"(d[42]), "+f"(d[43]), "+f"(d[44]), "+f"(d[45]), "+f"(d[46]), "+f"(d[47]),
      "+f"(d[48]), "+f"(d[49]), "+f"(d[50]), "+f"(d[51]), "+f"(d[52]), "+f"(d[53]), "+f"(d[54]), "+f"(d[55]),
      "+f"(d[56]), "+f"(d[57]), "+f"(d[58]), "+f"(d[59]), "+f"(d[60]), "+f"(d[61]), "+f"(d[62]), "+f"(d[63]),
      "+f"(d[64]), "+f"(d[65]), "+f"(d[66]), "+f"(d[67]), "+f"(d[68]), "+f"(d[69]), "+f"(d[70]), "+f"(d[71]),
      "+f"(d[72]), "+f"(d[73]), "+f"(d[74]), "+f"(d[75]), "+f"(d[76]), "+f"(d[77]), "+f"(d[78]), "+f"(d[79]),
      "+f"(d[80]), "+f"(d[81]), "+f"(d[82]), "+f"(d[83]), "+f"(d[84]), "+f"(d[85]), "+f"(d[86]), "+f"(d[87]),
      "+f"(d[88]), "+f"(d[89]), "+f"(d[90]), "+f"(d[91]), "+f"(d[92]), "+f"(d[93]), "+f"(d[94]), "+f"(d[95])
    : "l"(da), "l"(db), "r"(acc));
}
__device__ __forceinline__ void wg_ss_n64(float* d, uint64_t da, uint64_t db, int acc) {
  asm volatile("{.reg .pred p; setp.ne.b32 p, %34, 0;\n"
    "wgmma.mma_async.sync.aligned.m64n64k16.f32.bf16.bf16 {%0,%1,%2,%3,%4,%5,%6,%7,%8,%9,%10,%11,%12,%13,%14,%15,%16,%17,%18,%19,%20,%21,%22,%23,%24,%25,%26,%27,%28,%29,%30,%31}, %32, %33, p, 1, 1, 0, 1;}\n"
    : "+f"(d[0]), "+f"(d[1]), "+f"(d[2]), "+f"(d[3]), "+f"(d[4]), "+f"(d[5]), "+f"(d[6]), "+f"(d[7]),
      "+f"(d[8]), "+f"(d[9]), "+f"(d[10]), "+f"(d[11]), "+f"(d[12]), "+f"(d[13]), "+f"(d[14]), "+f"(d[15]),
      "+f"(d[16]), "+f"(d[17]), "+f"(d[18]), "+f"(d[19]), "+f"(d[20]), "+f"(d[21]), "+f"(d[22]), "+f"(d[23]),
      "+f"(d[24]), "+f"(d[25]), "+f"(d[26]), "+f"(d[27]), "+f"(d[28]), "+f"(d[29]), "+f"(d[30]), "+f"(d[31])
    : "l"(da), "l"(db), "r"(acc));
}

__device__ __forceinline__ void exp2_tile(const uint32_t* s, uint32_t* p, uint32_t cb, uint32_t cm, uint32_t ce) {
  constexpr int NS = 32 - NMU, L = 2, STEPS = NS + 3 * L + 2;
  const uint32_t* sw = s + NMU;
  uint32_t y[NS], m[NS], e[NS];
  uint16_t lo[NMU], hi[NMU];
  int issued = 0, packed = 0;
#pragma unroll
  for (int st = 0; st < STEPS; st++) {
    int tgt = ((st + 1) * NMU * 2 + NS - 1) / NS;
    if (tgt > NMU * 2) tgt = NMU * 2;
#pragma unroll
    for (int k = 0; k < 4; k++)
      if (issued < tgt) {
        int r = issued >> 1;
        if (issued & 1) asm volatile("{.reg .b16 a,b; mov.b32 {a,b}, %1; ex2.approx.f16 %0, b;}" : "=h"(hi[r]) : "r"(s[r]));
        else asm volatile("{.reg .b16 a,b; mov.b32 {a,b}, %1; ex2.approx.f16 %0, a;}" : "=h"(lo[r]) : "r"(s[r]));
        issued++;
      }
    if (st < NS) asm volatile("fma.rn.relu.f16x2 %0, %1, %2, %3;" : "=r"(y[st]) : "r"(sw[st]), "r"(0x00400040), "r"(cb));
    if (st >= L && st - L < NS) asm volatile("mul.lo.u32 %0, %0, 16;" : "+r"(y[st - L]));
    if (st >= 2 * L && st - 2 * L < NS) {
      int i = st - 2 * L;
      asm volatile("lop3.b32 %0, %1, 0x03ff03ff, %2, 0xEA;" : "=r"(m[i]) : "r"(y[i]), "r"(cm));
      asm volatile("lop3.b32 %0, %1, 0x7c007c00, %2, 0xEA;" : "=r"(e[i]) : "r"(y[i]), "r"(ce));
    }
    if (st >= 3 * L && st - 3 * L < NS) {
      int i = st - 3 * L;
      asm volatile("fma.rn.f16x2 %0, %1, %2, %3;" : "=r"(p[NMU + i]) : "r"(y[i]), "r"(m[i]), "r"(e[i]));
    }
    int tp = st >= 5 ? ((st - 4) * NMU * 2 + NS - 1) / NS / 2 : 0;
    if (tp > NMU || st == STEPS - 1) tp = NMU;
#pragma unroll
    for (int k = 0; k < 8; k++)
      if (packed < tp) {
        asm volatile("mov.b32 %0, {%1, %2};" : "=r"(p[packed]) : "h"(lo[packed]), "h"(hi[packed]));
        packed++;
      }
  }
}

constexpr uint64_t DV_STEP = (16ull << 32) - 16ull;

__device__ __forceinline__ void attn_true_max(uint32_t sb, uint4 qf, float* out) {
  uint32_t q[4] = {qf.x, qf.y, qf.z, qf.w}, s[32];
  float o[12];
#pragma unroll
  for (int i = 0; i < 12; i++) o[i] = 0.f;
  uint64_t dk = make_desc(sb + SM_K, 128, 256, 0), dv = make_desc(sb + SM_ONE - 256, 128, 256, 0);
  __half2 m0 = __float2half2_rn(-65504.f), m1 = m0;
#pragma unroll 1
  for (int it = 0; it < 16; it++) {
    wg_fence(); wg_qk(s, q, dk + it * 256); wg_commit(); wg_wait<0>(); pin<32>(s);
#pragma unroll
    for (int i = 0; i < 32; i += 2) { m0 = __hmax2(m0, *(__half2*)&s[i]); m1 = __hmax2(m1, *(__half2*)&s[i + 1]); }
  }
  m0 = __hmax2(m0, __lowhigh2highlow(m0)); m1 = __hmax2(m1, __lowhigh2highlow(m1));
#pragma unroll
  for (int d = 1; d < 4; d <<= 1) { m0 = __hmax2(m0, __shfl_xor_sync(~0u, m0, d)); m1 = __hmax2(m1, __shfl_xor_sync(~0u, m1, d)); }
  const __half2 up = __float2half2_rn(12.f);
#pragma unroll 1
  for (int it = 0; it < 16; it++) {
    wg_fence(); wg_qk(s, q, dk + it * 256); wg_commit(); wg_wait<0>(); pin<32>(s);
#pragma unroll
    for (int i = 0; i < 32; i++) {
      __half2 t = __hadd2(__hsub2(*(__half2*)&s[i], (i & 1) ? m1 : m0), up);
      asm("ex2.approx.f16x2 %0, %1;" : "=r"(s[i]) : "r"(*(uint32_t*)&t));
    }
    pin<32>(s); pin<12>(o);
    wg_fence();
#pragma unroll
    for (int j = 0; j < 8; j++) { wg_pv(o, s + j * 4, dv); dv += DV_STEP; }
    wg_commit(); wg_wait<0>(); pin<12>(o);
  }
#pragma unroll
  for (int i = 0; i < 12; i++) out[i] = o[i];
}

__device__ __noinline__ void attn_fp32(const bf16* x, const bf16* w, int h, int rt, int barid) {
  const int t = threadIdx.x & 127;
  float* kv = g_slow + (size_t)h * SEQ * 32;
  const int col = ((t & 31) >> 4) * DM + DM + h * 16 + (t & 15);
  for (int key = t >> 5; key < SEQ; key += 4) {
    float a = 0.f;
    for (int k = 0; k < DM; k++) a += __bfloat162float(x[key * DM + k]) * __bfloat162float(w[k * 3 * DM + col]);
    __stcg(kv + key * 32 + (t & 31), a);
  }
  __threadfence();
  bar_sync(barid, 128);
  if (t < 64) {
    float q[16], o[16], m = -INFINITY, l = 0.f;
#pragma unroll
    for (int d = 0; d < 16; d++) { q[d] = 0.f; o[d] = 0.f; }
    for (int k = 0; k < DM; k++) {
      float xv = __bfloat162float(x[(rt * 64 + t) * DM + k]);
#pragma unroll
      for (int d = 0; d < 16; d++) q[d] += xv * __bfloat162float(w[k * 3 * DM + h * 16 + d]);
    }
    for (int key = 0; key < SEQ; key++) {
      float sc = 0.f;
#pragma unroll
      for (int d = 0; d < 16; d++) sc += q[d] * __ldcg(kv + key * 32 + d);
      sc *= 0.25f;
      float mn = fmaxf(m, sc), c = __expf(m - mn), p = __expf(sc - mn);
      l = l * c + p; m = mn;
#pragma unroll
      for (int d = 0; d < 16; d++) o[d] = o[d] * c + p * __ldcg(kv + key * 32 + 16 + d);
    }
    float inv = 1.f / l;
    uint4* dst = g_o + (rt * NH + h) * 128 + (t >> 3) * 16 + (t & 7);
#pragma unroll
    for (int hf = 0; hf < 2; hf++)
      dst[hf * 8] = make_uint4(pack_b2(o[hf * 8] * inv, o[hf * 8 + 1] * inv), pack_b2(o[hf * 8 + 2] * inv, o[hf * 8 + 3] * inv),
                               pack_b2(o[hf * 8 + 4] * inv, o[hf * 8 + 5] * inv), pack_b2(o[hf * 8 + 6] * inv, o[hf * 8 + 7] * inv));
  }
}

__device__ __forceinline__ void fma8(float (*acc)[8], uint4 w, float2 xv) {
  const uint32_t u[4] = {w.x, w.y, w.z, w.w};
#pragma unroll
  for (int i = 0; i < 4; i++) {
    float a = b_lo(u[i]), b = b_hi(u[i]);
    acc[0][2 * i] += xv.x * a; acc[0][2 * i + 1] += xv.x * b;
    acc[1][2 * i] += xv.y * a; acc[1][2 * i + 1] += xv.y * b;
  }
}
__device__ __noinline__ void ffn_cta(const Params& P, uint8_t* sm, int f, uint32_t epoch) {
  const int tid = threadIdx.x, lane = tid & 31, warp = tid >> 5;
  unsigned long long* red = (unsigned long long*)sm;
  float2* xs = (float2*)(sm + 256);
  float2* hs = (float2*)(sm + 256 + 4096);
  float* part = (float*)(sm + 256 + 8192);
  unsigned long long key[4], best[2];
#pragma unroll
  for (int i = 0; i < 4; i++) {
    uint32_t u = cell_get(g_r + i * NTHR + tid, epoch);
    u = (u & 0x80000000u) ? ~u : (u | 0x80000000u);
    key[i] = ((unsigned long long)u << 32) | (uint32_t)(SEQ - 1 - (i * NTHR + tid));
  }
  if (tid < 28) {
    const void* src = P.wd + (size_t)(f * FSL + tid * 16) * DM;
    asm volatile("cp.async.bulk.prefetch.L2.global [%0], %1;" ::"l"(src), "r"(16 * DM * 2) : "memory");
  }
#pragma unroll
  for (int r = 0; r < 2; r++) {
    unsigned long long b = 0;
#pragma unroll
    for (int i = 0; i < 4; i++) if (!(r == 1 && key[i] == best[0]) && key[i] > b) b = key[i];
#pragma unroll
    for (int d = 16; d; d >>= 1) { unsigned long long o = __shfl_xor_sync(~0u, b, d); b = o > b ? o : b; }
    __syncthreads();
    if (lane == 0) red[warp] = b;
    __syncthreads();
#pragma unroll
    for (int i = 0; i < 16; i++) b = red[i] > b ? red[i] : b;
    best[r] = b;
  }
  const int i0 = SEQ - 1 - (int)(uint32_t)best[0], i1 = SEQ - 1 - (int)(uint32_t)best[1];
  xs[tid] = make_float2(__bfloat162float(P.x[i0 * DM + tid]), __bfloat162float(P.x[i1 * DM + tid]));
  __syncthreads();
  float acc[2][8];
  if (tid < 448) {
    const int rg = tid / 112, c = tid % 112, mat = c / 56, c8 = c % 56;
    const uint4* w = (const uint4*)((mat ? P.wu : P.wg) + (size_t)rg * 128 * FF + f * FSL + c8 * 8);
#pragma unroll
    for (int i = 0; i < 8; i++) acc[0][i] = acc[1][i] = 0.f;
#pragma unroll 1
    for (int k0 = 0; k0 < 128; k0 += 16) {
      uint4 v[16];
#pragma unroll
      for (int k = 0; k < 16; k++) v[k] = __ldg(w + (size_t)(k0 + k) * (FF / 8));
#pragma unroll
      for (int k = 0; k < 16; k++) fma8(acc, v[k], xs[rg * 128 + k0 + k]);
    }
#pragma unroll
    for (int t = 0; t < 2; t++)
#pragma unroll
      for (int i = 0; i < 8; i++) part[((rg * 2 + mat) * 2 + t) * FSL + c8 * 8 + i] = acc[t][i];
  }
  __syncthreads();
  if (tid < FSL) {
    float hv[2];
#pragma unroll
    for (int t = 0; t < 2; t++) {
      float a = 0.f, u = 0.f;
#pragma unroll
      for (int rg = 0; rg < 4; rg++) { a += part[((rg * 2) * 2 + t) * FSL + tid]; u += part[((rg * 2 + 1) * 2 + t) * FSL + tid]; }
      hv[t] = a * sigmoidf(a) * u;
    }
    hs[tid] = make_float2(hv[0], hv[1]);
  }
  __syncthreads();
  {
    const int rg = tid >> 6, c8 = tid & 63;
    const uint4* w = (const uint4*)(P.wd + (size_t)(f * FSL + rg * 56) * DM + c8 * 8);
#pragma unroll
    for (int i = 0; i < 8; i++) acc[0][i] = acc[1][i] = 0.f;
#pragma unroll 1
    for (int k0 = 0; k0 < 56; k0 += 14) {
      uint4 v[14];
#pragma unroll
      for (int k = 0; k < 14; k++) v[k] = __ldg(w + (size_t)(k0 + k) * (DM / 8));
#pragma unroll
      for (int k = 0; k < 14; k++) fma8(acc, v[k], hs[rg * 56 + k0 + k]);
    }
#pragma unroll
    for (int t = 0; t < 2; t++)
#pragma unroll
      for (int i = 0; i < 8; i++) part[(rg * 2 + t) * DM + c8 * 8 + i] = acc[t][i];
  }
  __syncthreads();
#pragma unroll
  for (int t = 0; t < 2; t++) {
    float a = 0.f;
#pragma unroll
    for (int rg = 0; rg < 8; rg++) a += part[(rg * 2 + t) * DM + tid];
    uint32_t u = (uint32_t)(best[t] >> 32);
    u = (u & 0x80000000u) ? (u & 0x7fffffffu) : ~u;
    g_y[(f * 2 + t) * DM + tid] = a * sigmoidf(__uint_as_float(u));
  }
  __syncthreads();
  if (tid == 0) {
    __threadfence();
    cell_set(g_fy + f, (uint32_t)i0 | ((uint32_t)i1 << 16), epoch);
  }
}

__global__ void __launch_bounds__(NTHR, 1)
fused_kernel(const __grid_constant__ CUtensorMap tm_x, const __grid_constant__ CUtensorMap tm_w,
             const __grid_constant__ CUtensorMap tm_wo, const __grid_constant__ CUtensorMap tm_out,
             const __grid_constant__ Params P) {
  extern __shared__ uint8_t smem_raw[];
  const uint32_t sraw = (uint32_t)__cvta_generic_to_shared(smem_raw);
  const uint32_t sb = (sraw + 1023) & ~1023u;
  uint8_t* sm = smem_raw + (sb - sraw);
  const uint32_t bars = sb + SM_BAR;
  const int tid = threadIdx.x, lane = tid & 31, wg = tid >> 7, wi = (tid >> 5) & 3;
  const int cta = blockIdx.x;
  TSTAMP(0, tid == 0)
  const int hg = cta >> 4, tm = cta & 15;
  if (tid == 256 && cta < NMAIN) {
#pragma unroll 1
    for (int i = 0; i < B_N; i++) mbar_init(bars + i * 8, (i >= B_EMPTY && i < B_KV) ? 2 : (i >= B_A ? 8 : (i == B_Q ? 4 : 1)));
    asm volatile("fence.mbarrier_init.release.cluster;" ::: "memory");
    fence_async();
#pragma unroll 1
    for (int kc = 0; kc < NSTAGE; kc++) {
      const uint32_t st = sb + kc * STG, bar = bars + (B_FULL + kc) * 8;
      mbar_expect(bar, STG);
      tma2d(st, &tm_x, kc * 64, tm * 128, bar);
#pragma unroll
      for (int j = 0; j < 3; j++) tma2d(st + STG_A + j * 8192, &tm_w, j * DM + hg * 64, kc * 64, bar);
    }
  }
  const uint32_t epoch = __ldcg(g_epoch + cta) + 1;
  __syncthreads();
  if (cta >= NMAIN) {
    ffn_cta(P, sm, cta - NMAIN, epoch);
    if (tid == 0) g_epoch[cta] = epoch;
    TSTAMP(7, tid == 0)
    return;
  }
  const int h = cta >> 2, qc = cta & 3;
  const int rt3 = qc * 8 + (h >> 2), cs = h & 3;

  if (wg < 2) {
    float acc[96];
#pragma unroll 1
    for (int kc = 0; kc < 8; kc++) {
      const int s = kc >= NSTAGE ? kc - NSTAGE : kc;
      mbar_wait(bars + (B_FULL + s) * 8, kc >= NSTAGE);
      TSTAMP(1, tid == 0 && kc == 0)
      const uint64_t da = make_desc(sb + s * STG + wg * 8192, 16, 1024, 1), db = make_desc(sb + s * STG + STG_A, 8192, 1024, 1);
      wg_fence();
#pragma unroll
      for (int ks = 0; ks < 4; ks++) wg_ss_n192(acc, da + ks * 2, db + ks * 128, kc | ks);
      wg_commit();
      wg_wait<1>();
      if (kc >= 1 && kc <= 8 - NSTAGE && (tid & 127) == 0) mbar_arrive(bars + (B_EMPTY + kc - 1) * 8);
    }
    wg_wait<0>();
    pin<96>(acc);
    TSTAMP(2, tid == 0)
    const int step = tm * 8 + wg * 4 + wi;
    constexpr float QS = 0.25f * 1.4426950408889634f;
    uint32_t kk[16], vv[16];
#pragma unroll
    for (int i = 0; i < 16; i++) { kk[i] = pack_h2(acc[32 + 2 * i], acc[33 + 2 * i]); vv[i] = pack_h2(acc[64 + 2 * i], acc[65 + 2 * i]); }
#pragma unroll
    for (int hl = 0; hl < 4; hl++) {
      const int hh = hg * 4 + hl;
      uint32_t* kp = (uint32_t*)(g_k + hh * 4096 + step * 32) + lane;
      kp[0] = kk[hl * 4]; kp[64] = kk[hl * 4 + 1]; kp[32] = kk[hl * 4 + 2]; kp[96] = kk[hl * 4 + 3];
      uint32_t* v0 = (uint32_t*)(g_v0 + hh * 2048 + (127 - step) * 16) + lane;
      uint32_t* v1 = (uint32_t*)(g_v1 + hh * 2048 + step * 16) + lane;
      v0[0] = vv[hl * 4]; v0[32] = vv[hl * 4 + 1]; v1[0] = vv[hl * 4 + 2]; v1[32] = vv[hl * 4 + 3];
      const float* a = acc + hl * 8;
      g_q[hh * 4096 + step * 32 + lane] = make_uint4(pack_h2(a[0] * QS, a[1] * QS), pack_h2(a[2] * QS, a[3] * QS),
                                                     pack_h2(a[4] * QS, a[5] * QS), pack_h2(a[6] * QS, a[7] * QS));
    }
    bar_sync(1 + wg, 128);
    if ((tid & 127) == 0) flag_set(g_f1 + hg * 32 + tm * 2 + wg, epoch);
    TSTAMP(3, tid == 0)
#pragma unroll
    for (int hl = 0; hl < 4; hl++) {
      const float* k = acc + 32 + hl * 8;
      const float* v = acc + 64 + hl * 8;
      float n0 = k[0] * k[0] + k[1] * k[1] + k[4] * k[4] + k[5] * k[5], n1 = k[2] * k[2] + k[3] * k[3] + k[6] * k[6] + k[7] * k[7];
#pragma unroll
      for (int d = 1; d < 4; d <<= 1) { n0 += __shfl_xor_sync(~0u, n0, d); n1 += __shfl_xor_sync(~0u, n1, d); }
      uint32_t vm = 0;
#pragma unroll
      for (int i = 0; i < 8; i++) vm = max(vm, __float_as_uint(v[i]) & 0x7fffffffu);
      const uint32_t kn = __reduce_max_sync(~0u, max(__float_as_uint(n0) & 0x7fffffffu, __float_as_uint(n1) & 0x7fffffffu));
      vm = __reduce_max_sync(~0u, vm);
      if (lane == 0) cell_set(g_stat + (hg * 4 + hl) * 128 + step, min((kn >> 16) + 1, 0x7fffu) | (vm & 0xffff0000u), epoch);
    }
  } else if (wg == 2) {
    if (wi == 0) {
      if (lane == 0) {
#pragma unroll 1
        for (int kc = NSTAGE; kc < 8; kc++) {
          const int s = kc - NSTAGE;
          const uint32_t st = sb + s * STG, bar = bars + (B_FULL + s) * 8;
          mbar_wait(bars + (B_EMPTY + s) * 8, 0);
          mbar_expect(bar, STG);
          tma2d(st, &tm_x, kc * 64, tm * 128, bar);
#pragma unroll
          for (int j = 0; j < 3; j++) tma2d(st + STG_A + j * 8192, &tm_w, j * DM + hg * 64, kc * 64, bar);
        }
      }
      __syncwarp();
      flag_wait(g_f1 + hg * 32 + lane, epoch);
      __syncwarp();
      TSTAMP(4, lane == 0)
      *(uint2*)(sm + SM_ONE + lane * 8) = make_uint2(0x3c003c00u, 0x3c003c00u);
      fence_async();
      __syncwarp();
      if (lane < 4) {
        mbar_expect(bars + B_Q * 8, 4096);
        bulk(sb + SM_Q + lane * 4096, g_q + h * 4096 + (qc * 4 + lane) * 256, 4096, bars + B_Q * 8);
      }
      __syncwarp();
      if (lane < 16) {
        const uint32_t bar = bars + (B_KV + lane) * 8;
        mbar_expect(bar, 8192);
        bulk(sb + SM_K + lane * 4096, g_k + h * 4096 + lane * 256, 4096, bar);
        bulk(sb + SM_V0 + (15 - lane) * 2048, g_v0 + h * 2048 + (15 - lane) * 128, 2048, bar);
        bulk(sb + SM_V1 + lane * 2048, g_v1 + h * 2048 + lane * 128, 2048, bar);
      }
      __syncwarp();
      if (lane == 0) {
        mbar_expect(bars + B_WO0 * 8, 65536);
        tma2d(sb + SM_WO0, &tm_wo, cs * 128, 0, bars + B_WO0 * 8);
        tma2d(sb + SM_WO0 + 32768, &tm_wo, cs * 128 + 64, 0, bars + B_WO0 * 8);
      }
      __syncwarp();
    }
  } else {
    const uint4* wr = (const uint4*)P.wr; const uint4* gw = (const uint4*)P.gw;
    const int t0 = tm * 128 + hg * 16 + wi * 4;
    uint4 xv[4][2], a[2], b[2];
#pragma unroll
    for (int t = 0; t < 4; t++)
#pragma unroll
      for (int j = 0; j < 2; j++) xv[t][j] = __ldg((const uint4*)(P.x + (t0 + t) * DM) + j * 32 + lane);
#pragma unroll
    for (int j = 0; j < 2; j++) { a[j] = __ldg(wr + j * 32 + lane); b[j] = __ldg(gw + j * 32 + lane); }
#pragma unroll
    for (int t = 0; t < 4; t++) {
      float r = 0.f, g = 0.f;
#pragma unroll
      for (int j = 0; j < 2; j++) {
        const uint32_t xu[4] = {xv[t][j].x, xv[t][j].y, xv[t][j].z, xv[t][j].w};
        const uint32_t au[4] = {a[j].x, a[j].y, a[j].z, a[j].w}, bu[4] = {b[j].x, b[j].y, b[j].z, b[j].w};
#pragma unroll
        for (int i = 0; i < 4; i++) {
          r += b_lo(xu[i]) * b_lo(au[i]) + b_hi(xu[i]) * b_hi(au[i]);
          g += b_lo(xu[i]) * b_lo(bu[i]) + b_hi(xu[i]) * b_hi(bu[i]);
        }
      }
#pragma unroll
      for (int d = 16; d; d >>= 1) { r += __shfl_xor_sync(~0u, r, d); g += __shfl_xor_sync(~0u, g, d); }
      if (lane == 0) { cell_set(g_r + t0 + t, __float_as_uint(r), epoch); cell_set(g_g + t0 + t, __float_as_uint(sigmoidf(g)), epoch); }
    }
  }

  {
    uint32_t cb = 0x039a039au, cm = 0x38003800u, ce = 0x000b000bu;
    asm volatile("" : "+r"(cb), "+r"(cm), "+r"(ce));
    float kn2 = 0.f; bool range_bad = false;
    mbar_wait(bars + B_Q * 8, 0);
    TSTAMP(5, tid == 0)
#pragma unroll 1
    for (int pass = 0; pass < 2; pass++) {
      const uint4 qf = *(const uint4*)(sm + SM_Q + wg * 4096 + (pass * 4 + wi) * 512 + lane * 16);
      uint32_t q[4] = {qf.x, qf.y, qf.z, qf.w}, s[32], p[32];
      float o[12];
#pragma unroll
      for (int i = 0; i < 12; i++) o[i] = 0.f;
      uint64_t dk = make_desc(sb + SM_K, 128, 256, 0), dv = make_desc(sb + SM_ONE - 256, 128, 256, 0);
      mbar_wait(bars + B_KV * 8, 0);
      pin<12>(o);
      wg_fence(); wg_qk(s, q, dk); wg_commit(); wg_wait<0>(); pin<32>(s);
#pragma unroll 1
      for (int it = 0; it < 16; it++) {
        wg_wait<0>();
        exp2_tile(s, p, cb, cm, ce);
        mbar_wait(bars + (B_KV + 1 + it) * 8, 0);
        wg_fence();
        dk += 256;
        wg_qk(s, q, dk);
        wg_commit();
#pragma unroll
        for (int j = 0; j < 8; j++) { wg_pv(o, p + j * 4, dv); dv += DV_STEP; }
        wg_commit();
        wg_wait<1>();
        pin<32>(s);
      }
      wg_wait<0>();
      pin<12>(o);
      if (pass == 0) {
        uint32_t a = 0, b = 0;
#pragma unroll
        for (int i = 0; i < 4; i++) { const uint32_t u = cell_get(g_stat + h * 128 + i * 32 + lane, epoch); a = max(a, u & 0xffffu); b = max(b, u >> 16); }
        kn2 = __uint_as_float(__reduce_max_sync(~0u, a) << 16);
        const float vm = __uint_as_float(__reduce_max_sync(~0u, b) << 16);
        range_bad = !(kn2 <= 1.6e7f && vm >= 6.2e-5f && vm <= 6.0e4f);
      }
      float n0 = h_lo(q[0]) * h_lo(q[0]) + h_hi(q[0]) * h_hi(q[0]) + h_lo(q[2]) * h_lo(q[2]) + h_hi(q[2]) * h_hi(q[2]);
      float n1 = h_lo(q[1]) * h_lo(q[1]) + h_hi(q[1]) * h_hi(q[1]) + h_lo(q[3]) * h_lo(q[3]) + h_hi(q[3]) * h_hi(q[3]);
#pragma unroll
      for (int d = 1; d < 4; d <<= 1) { n0 += __shfl_xor_sync(~0u, n0, d); n1 += __shfl_xor_sync(~0u, n1, d); }
      const bool safe = !range_bad && n0 * kn2 <= 289.f && n1 * kn2 <= 289.f && n0 <= 1.6e7f && n1 <= 1.6e7f &&
                        o[4] >= 64.f && o[4] <= 1e30f && o[6] >= 64.f && o[6] <= 1e30f;
      const int rt = qc * 8 + wg * 2 + pass;
      uint32_t* op = (uint32_t*)(g_o + (rt * NH + h) * 128 + wi * 32) + lane;
      float i0 = 1.f / o[4], i1 = 1.f / o[6];
      op[0] = pack_b2(o[0] * i0, o[1] * i0); op[64] = pack_b2(o[2] * i1, o[3] * i1);
      op[32] = pack_b2(o[8] * i0, o[9] * i0); op[96] = pack_b2(o[10] * i1, o[11] * i1);
      if (bar_or(1 + wg, 128, !safe)) {
        if (bar_or(1 + wg, 128, range_bad || !(n0 * kn2 <= 9e8f && n1 * kn2 <= 9e8f && n0 <= 1.6e7f && n1 <= 1.6e7f))) {
          attn_fp32(P.x, P.wqkv, h, rt, 1 + wg);
        } else {
          float r[12];
          attn_true_max(sb, qf, r);
          i0 = 1.f / r[4]; i1 = 1.f / r[6];
          op[0] = pack_b2(r[0] * i0, r[1] * i0); op[64] = pack_b2(r[2] * i1, r[3] * i1);
          op[32] = pack_b2(r[8] * i0, r[9] * i0); op[96] = pack_b2(r[10] * i1, r[11] * i1);
        }
        bar_sync(1 + wg, 128);
      }
      if ((tid & 127) == 0) flag_set(g_f2 + rt * NH + h, epoch);
    }
  }
  TSTAMP(6, tid == 0)

  if (wg == 2) {
    bar_sync(5, NTHR);
    if (wi == 0) {
      if (lane == 0) {
        mbar_expect(bars + B_WO1 * 8, 65536);
        tma2d(sb + SM_WO1, &tm_wo, cs * 128, 256, bars + B_WO1 * 8);
        tma2d(sb + SM_WO1 + 32768, &tm_wo, cs * 128 + 64, 256, bars + B_WO1 * 8);
      }
      __syncwarp();
      flag_wait(g_f2 + rt3 * NH + lane, epoch);
      fence_async();
      const uint32_t bar = bars + (B_A + (lane >> 3)) * 8;
      mbar_expect(bar, 2048);
      bulk(sb + SM_A + lane * 2048, g_o + (rt3 * NH + lane) * 128, 2048, bar);
      TSTAMP(8, lane == 0)
    }
  } else {
    bar_arrive(5, NTHR);
  }
  if (wg < 2) {
    const int r0 = rt3 * 64 + wi * 16 + (lane >> 2), c0 = cs * 128 + wg * 64 + (lane & 3) * 2;
    uint32_t xr[16];
#pragma unroll
    for (int i = 0; i < 16; i++) xr[i] = __ldg((const uint32_t*)(P.x + (r0 + (i & 1) * 8) * DM + c0 + (i >> 1) * 8));
    const float g0 = __uint_as_float(cell_get(g_g + r0, epoch)), g1 = __uint_as_float(cell_get(g_g + r0 + 8, epoch));
    const uint32_t idx = cell_get(g_fy + (lane & 3), epoch);
    __syncwarp();
    float pre[32], acc[32];
#pragma unroll
    for (int i = 0; i < 16; i++) { pre[2 * i] = b_lo(xr[i]); pre[2 * i + 1] = b_hi(xr[i]); }
#pragma unroll
    for (int t = 0; t < 2; t++) {
      const int d = (int)((idx >> (16 * t)) & 0xffff) - r0;
      if (d == 0 || d == 8) {
        __threadfence();
#pragma unroll
        for (int nb = 0; nb < 8; nb++) {
          float u0 = 0.f, u1 = 0.f;
#pragma unroll
          for (int f = 0; f < NFFN; f++) { const float2 y = __ldcg((const float2*)(g_y + (f * 2 + t) * DM + c0 + nb * 8)); u0 += y.x; u1 += y.y; }
          if (d == 0) { pre[nb * 4] += u0; pre[nb * 4 + 1] += u1; } else { pre[nb * 4 + 2] += u0; pre[nb * 4 + 3] += u1; }
        }
      }
    }
    __syncwarp();
#pragma unroll
    for (int i = 0; i < 32; i++) pre[i] *= 1.f - ((i & 2) ? g1 : g0);
    pin<32>(pre);
    mbar_wait(bars + B_WO0 * 8, 0);
#pragma unroll 1
    for (int c = 0; c < 4; c++) {
      if (c == 2) mbar_wait(bars + B_WO1 * 8, 0);
      mbar_wait(bars + (B_A + c) * 8, 0);
      const uint64_t da = make_desc(sb + SM_A + c * 16384, 128, 256, 0);
      const uint64_t db = make_desc(sb + (c < 2 ? SM_WO0 : SM_WO1) + wg * 32768 + (c & 1) * 16384, 8192, 1024, 1);
      wg_fence();
#pragma unroll
      for (int ks = 0; ks < 8; ks++) wg_ss_n64(acc, da + ks * 128, db + ks * 128, c | ks);
      wg_commit();
    }
    wg_wait<0>();
    pin<32>(acc);
    TSTAMP(9, tid == 0)
    const uint32_t stg = sb + SM_OUT + (wg * 4 + wi) * 2048;
    const int row = lane & 15;
#pragma unroll
    for (int j = 0; j < 4; j++) {
      uint32_t r[4];
#pragma unroll
      for (int i = 0; i < 4; i++) {
        const int k = j * 8 + i * 2; const float g = (i & 1) ? g1 : g0;
        r[i] = pack_b2(fmaf(g, acc[k], pre[k]), fmaf(g, acc[k + 1], pre[k + 1]));
      }
      const uint32_t a = stg + row * 128 + (((j * 2 + (lane >> 4)) ^ (row & 7)) << 4);
      asm volatile("stmatrix.sync.aligned.m8n8.x4.shared.b16 [%0], {%1, %2, %3, %4};" ::"r"(a), "r"(r[0]), "r"(r[1]), "r"(r[2]), "r"(r[3]) : "memory");
    }
    fence_async();
    __syncwarp();
    if (lane == 0) {
      asm volatile("cp.async.bulk.tensor.2d.global.shared::cta.bulk_group [%0, {%2, %3}], [%1];"
        ::"l"(&tm_out), "r"(stg), "r"(cs * 128 + wg * 64), "r"(rt3 * 64 + wi * 16) : "memory");
      asm volatile("cp.async.bulk.commit_group;" ::: "memory");
      asm volatile("cp.async.bulk.wait_group.read 0;" ::: "memory");
    }
    if (tid == 0) g_epoch[cta] = epoch;
    TSTAMP(7, tid == 0)
  }
}

typedef CUresult (*EncodeFn)(CUtensorMap*, CUtensorMapDataType, cuuint32_t, void*, const cuuint64_t*, const cuuint64_t*,
                             const cuuint32_t*, const cuuint32_t*, CUtensorMapInterleave, CUtensorMapSwizzle,
                             CUtensorMapL2promotion, CUtensorMapFloatOOBfill);
static void make_map(EncodeFn enc, CUtensorMap* m, const void* p, int cols, int rows, int box_rows) {
  cuuint64_t dim[2] = {(cuuint64_t)cols, (cuuint64_t)rows}, str[1] = {(cuuint64_t)cols * 2};
  cuuint32_t box[2] = {64, (cuuint32_t)box_rows}, es[2] = {1, 1};
  enc(m, CU_TENSOR_MAP_DATA_TYPE_BFLOAT16, 2, (void*)p, dim, str, box, es, CU_TENSOR_MAP_INTERLEAVE_NONE,
      CU_TENSOR_MAP_SWIZZLE_128B, CU_TENSOR_MAP_L2_PROMOTION_L2_128B, CU_TENSOR_MAP_FLOAT_OOB_FILL_NONE);
}

extern "C" void kernel_launch(void* const* d_in, const int* in_sizes, int n_in, void* d_out, int out_size) {
  static EncodeFn enc = nullptr;
  if (!enc) {
    void* fn = nullptr; cudaDriverEntryPointQueryResult qr;
    cudaGetDriverEntryPoint("cuTensorMapEncodeTiled", &fn, cudaEnableDefault, &qr);
    enc = (EncodeFn)fn;
    cudaFuncSetAttribute(fused_kernel, cudaFuncAttributeMaxDynamicSharedMemorySize, SM_TOTAL);
  }
  CUtensorMap mx, mw, mwo, mo;
  make_map(enc, &mx, d_in[0], DM, SEQ, 128);
  make_map(enc, &mw, d_in[1], 3 * DM, DM, 64);
  make_map(enc, &mwo, d_in[2], DM, DM, 256);
  make_map(enc, &mo, d_out, DM, SEQ, 16);
  Params P;
  P.x = (const bf16*)d_in[0]; P.wqkv = (const bf16*)d_in[1]; P.wr = (const bf16*)d_in[4]; P.wg = (const bf16*)d_in[5];
  P.wu = (const bf16*)d_in[6]; P.wd = (const bf16*)d_in[7]; P.gw = (const bf16*)d_in[8];
  fused_kernel<<<NCTA, NTHR, SM_TOTAL, cudaStreamPerThread>>>(mx, mw, mwo, mo, P);
}
```

```cpp
#include <cuda_runtime.h>
#include <cuda.h>
#include <cuda_bf16.h>
#include <cuda_fp16.h>
#include <stdint.h>

typedef __nv_bfloat16 bf16;

constexpr int SEQ = 2048, DM = 512, NH = 32, FF = 1792;
constexpr int NMAIN = 128, NFFN = 4, NCTA = NMAIN + NFFN, NTHR = 640;
constexpr float QS = 0.25f * 1.4426950408889634f;
constexpr int FSL = FF / NFFN;
#define NMU 11
#define ORD 2
#define SHM 4

constexpr int NSTAGE = 5, STG_A = 32768, STG = STG_A + 12288;
constexpr int SLOT = 8192, NSLOT = 24;
constexpr int SM_OA = NSLOT * SLOT, SM_ONE = SM_OA + 32768, SM_BAR = SM_ONE + 512, SM_STAT = SM_BAR + 256;
constexpr int SM_OB = 0, SM_OUT = 32768, SM_WO = 65536;
constexpr int SM_TOTAL = SM_STAT + 128 + 1024;
constexpr int FSTG = 32768, FNS = 6, SM_XS = FNS * FSTG, SM_HS = SM_XS + 8192, SM_RED = SM_HS + 8192;
constexpr int B_FULL = 0, B_EMPTY = 6, B_KV = 12, B_FREE0 = 17, B_ORDY = 18, B_FREE1 = 19, B_DONE = 20, B_WO = 21, B_OA = 22, B_OB = 23, B_N = 27;

__device__ uint4 g_kv[NH * 16 * 512];
__device__ uint4 g_o[32 * NH * 128];
__device__ uint4 g_f1[NMAIN];
__device__ uint32_t g_f2[NMAIN];
__device__ uint2 g_r[SEQ], g_g[SEQ];
__device__ float g_y[NFFN * 2 * DM];
__device__ uint2 g_fy[NFFN];
__device__ uint32_t g_epoch[NCTA];
#define TSTAMP(i, cond)

struct Params {
  CUtensorMap x, w, wo, out, wg, wu, wd;
  const bf16 *px, *pw, *pwo, *pwr, *pgw;
};

constexpr uint32_t SPIN_LIMIT = 1u << 21;
__device__ __forceinline__ void wg_fence() { asm volatile("wgmma.fence.sync.aligned;" ::: "memory"); }
__device__ __forceinline__ void wg_commit() { asm volatile("wgmma.commit_group.sync.aligned;" ::: "memory"); }
template <int N> __device__ __forceinline__ void wg_wait() { asm volatile("wgmma.wait_group.sync.aligned %0;" ::"n"(N) : "memory"); }
template <int N> __device__ __forceinline__ void pin(uint32_t* s) {
#pragma unroll
  for (int i = 0; i < N; i++) asm volatile("" : "+r"(s[i])::"memory");
}
template <int N> __device__ __forceinline__ void pin(float* s) {
#pragma unroll
  for (int i = 0; i < N; i++) asm volatile("" : "+f"(s[i])::"memory");
}
__device__ __forceinline__ bool elect() {
  uint32_t p;
  asm volatile("{.reg .pred p; elect.sync _|p, 0xffffffff; selp.u32 %0, 1, 0, p;}" : "=r"(p));
  return p;
}
__device__ __forceinline__ void mbar_init(uint32_t bar, uint32_t cnt) { asm volatile("mbarrier.init.shared::cta.b64 [%0], %1;" ::"r"(bar), "r"(cnt) : "memory"); }
__device__ __forceinline__ void mbar_expect(uint32_t bar, uint32_t bytes) { asm volatile("mbarrier.arrive.expect_tx.shared::cta.b64 _, [%0], %1;" ::"r"(bar), "r"(bytes) : "memory"); }
__device__ __forceinline__ void mbar_arrive(uint32_t bar) { asm volatile("mbarrier.arrive.shared::cta.b64 _, [%0];" ::"r"(bar) : "memory"); }
__device__ __forceinline__ void mbar_wait(uint32_t bar, uint32_t parity) {
  asm volatile("{.reg .pred p; .reg .b32 c;\n"
    "mbarrier.try_wait.parity.shared::cta.b64 p, [%0], %1;\n"
    "@p bra.uni DONE;\n"
    "mov.b32 c, 0;\n"
    "LOOP: mbarrier.try_wait.parity.shared::cta.b64 p, [%0], %1, 1000;\n"
    "@p bra.uni DONE;\n"
    "add.u32 c, c, 1;\n"
    "setp.lt.u32 p, c, %2;\n"
    "@p bra.uni LOOP;\n"
    "DONE: }" ::"r"(bar), "r"(parity), "n"(SPIN_LIMIT) : "memory");
}
__device__ __forceinline__ void tma2d(uint32_t dst, const CUtensorMap* m, int c0, int c1, uint32_t bar) {
  asm volatile("cp.async.bulk.tensor.2d.shared::cluster.global.mbarrier::complete_tx::bytes [%0], [%1, {%3, %4}], [%2];"
    ::"r"(dst), "l"(m), "r"(bar), "r"(c0), "r"(c1) : "memory");
}
__device__ __forceinline__ void tma3d(uint32_t dst, const CUtensorMap* m, int c0, int c1, int c2, uint32_t bar) {
  asm volatile("cp.async.bulk.tensor.3d.shared::cluster.global.mbarrier::complete_tx::bytes [%0], [%1, {%3, %4, %5}], [%2];"
    ::"r"(dst), "l"(m), "r"(bar), "r"(c0), "r"(c1), "r"(c2) : "memory");
}
__device__ __forceinline__ void bulk(uint32_t dst, const void* src, uint32_t bytes, uint32_t bar) {
  asm volatile("cp.async.bulk.shared::cluster.global.mbarrier::complete_tx::bytes [%0], [%1], %2, [%3];"
    ::"r"(dst), "l"(src), "r"(bytes), "r"(bar) : "memory");
}
__device__ __forceinline__ void bulk_out(void* dst, uint32_t src, uint32_t bytes) {
  asm volatile("cp.async.bulk.global.shared::cta.bulk_group [%0], [%1], %2;" ::"l"(dst), "r"(src), "r"(bytes) : "memory");
}
__device__ __forceinline__ void fence_async() { asm volatile("fence.proxy.async.shared::cta;" ::: "memory"); }
__device__ __forceinline__ void fence_async_g() { asm volatile("fence.proxy.async.global;" ::: "memory"); }
__device__ __forceinline__ void bar_sync(int id, int n) { asm volatile("bar.sync %0, %1;" ::"r"(id), "r"(n) : "memory"); }
__device__ __forceinline__ void bar_arrive(int id, int n) { asm volatile("bar.arrive %0, %1;" ::"r"(id), "r"(n) : "memory"); }
__device__ __forceinline__ void stsm4(uint32_t a, const uint32_t* r) {
  asm volatile("stmatrix.sync.aligned.m8n8.x4.shared.b16 [%0], {%1, %2, %3, %4};" ::"r"(a), "r"(r[0]), "r"(r[1]), "r"(r[2]), "r"(r[3]) : "memory");
}
__device__ __forceinline__ void cell_set(uint2* p, uint32_t v, uint32_t e) { asm volatile("st.relaxed.gpu.global.v2.u32 [%0], {%1, %2};" ::"l"(p), "r"(v), "r"(e) : "memory"); }
__device__ __forceinline__ unsigned long long cell_ld(const uint2* p) {
  unsigned long long v;
  asm volatile("ld.relaxed.gpu.global.u64 %0, [%1];" : "=l"(v) : "l"(p) : "memory");
  return v;
}
__device__ __forceinline__ uint32_t cell_fin(const uint2* p, unsigned long long v, uint32_t e) {
  for (uint32_t c = 0; !__all_sync(~0u, (uint32_t)(v >> 32) == e); c++) {
    if (c > SPIN_LIMIT) break;
    v = cell_ld(p);
  }
  return (uint32_t)v;
}
__device__ __forceinline__ uint64_t make_desc(uint32_t addr, uint32_t lbo, uint32_t sbo, uint32_t swz) {
  return (uint64_t)((addr & 0x3FFFF) >> 4) | ((uint64_t)(lbo >> 4) << 16) | ((uint64_t)(sbo >> 4) << 32) | ((uint64_t)swz << 62);
}
__device__ __forceinline__ uint32_t pack_h2(float lo, float hi) { uint32_t r; asm("cvt.rn.f16x2.f32 %0, %1, %2;" : "=r"(r) : "f"(hi), "f"(lo)); return r; }
__device__ __forceinline__ uint32_t pack_b2(float lo, float hi) { uint32_t r; asm("cvt.rn.bf16x2.f32 %0, %1, %2;" : "=r"(r) : "f"(hi), "f"(lo)); return r; }
__device__ __forceinline__ float b_lo(uint32_t v) { return __uint_as_float(v << 16); }
__device__ __forceinline__ float b_hi(uint32_t v) { return __uint_as_float(v & 0xffff0000u); }
__device__ __forceinline__ float h_lo(uint32_t v) { return __half2float(__ushort_as_half((unsigned short)(v & 0xffff))); }
__device__ __forceinline__ float h_hi(uint32_t v) { return __half2float(__ushort_as_half((unsigned short)(v >> 16))); }
__device__ __forceinline__ float sigmoidf(float v) { return 1.f / (1.f + __expf(-v)); }
__device__ __forceinline__ void o_store(uint32_t* p, uint32_t v) {
  asm volatile("st.relaxed.gpu.global.u32 [%0], %1;" ::"l"(p), "r"(v ? v : 0x8000u) : "memory");
}

__device__ __forceinline__ void wg_qk(uint32_t* d, const uint32_t* a, uint64_t desc) {
  asm volatile("{.reg .pred p; setp.ne.b32 p, 0, 0;\n"
    "wgmma.mma_async.sync.aligned.m64n128k16.f16.f16.f16 {%0,%1,%2,%3,%4,%5,%6,%7,%8,%9,%10,%11,%12,%13,%14,%15,%16,%17,%18,%19,%20,%21,%22,%23,%24,%25,%26,%27,%28,%29,%30,%31}, {%32,%33,%34,%35}, %36, p, 1, 1, 0;}\n"
    : "=r"(d[0]), "=r"(d[1]), "=r"(d[2]), "=r"(d[3]), "=r"(d[4]), "=r"(d[5]), "=r"(d[6]), "=r"(d[7]),
      "=r"(d[8]), "=r"(d[9]), "=r"(d[10]), "=r"(d[11]), "=r"(d[12]), "=r"(d[13]), "=r"(d[14]), "=r"(d[15]),
      "=r"(d[16]), "=r"(d[17]), "=r"(d[18]), "=r"(d[19]), "=r"(d[20]), "=r"(d[21]), "=r"(d[22]), "=r"(d[23]),
      "=r"(d[24]), "=r"(d[25]), "=r"(d[26]), "=r"(d[27]), "=r"(d[28]), "=r"(d[29]), "=r"(d[30]), "=r"(d[31])
    : "r"(a[0]), "r"(a[1]), "r"(a[2]), "r"(a[3]), "l"(desc));
}
__device__ __forceinline__ void wg_pv(uint32_t* d, const uint32_t* a, uint64_t desc) {
  asm volatile("{.reg .pred p; setp.eq.b32 p, 0, 0;\n"
    "wgmma.mma_async.sync.aligned.m64n24k16.f16.f16.f16 {%0,%1,%2,%3,%4,%5}, {%6,%7,%8,%9}, %10, p, 1, 1, 1;}\n"
    : "+r"(d[0]), "+r"(d[1]), "+r"(d[2]), "+r"(d[3]), "+r"(d[4]), "+r"(d[5])
    : "r"(a[0]), "r"(a[1]), "r"(a[2]), "r"(a[3]), "l"(desc));
}
__device__ __forceinline__ void wg_ss_n96(float* d, uint64_t da, uint64_t db, int acc) {
  asm volatile("{.reg .pred p; setp.ne.b32 p, %50, 0;\n"
    "wgmma.mma_async.sync.aligned.m64n96k16.f32.bf16.bf16 {%0,%1,%2,%3,%4,%5,%6,%7,%8,%9,%10,%11,%12,%13,%14,%15,%16,%17,%18,%19,%20,%21,%22,%23,%24,%25,%26,%27,%28,%29,%30,%31,%32,%33,%34,%35,%36,%37,%38,%39,%40,%41,%42,%43,%44,%45,%46,%47}, %48, %49, p, 1, 1, 0, 1;}\n"
    : "+f"(d[0]), "+f"(d[1]), "+f"(d[2]), "+f"(d[3]), "+f"(d[4]), "+f"(d[5]), "+f"(d[6]), "+f"(d[7]),
      "+f"(d[8]), "+f"(d[9]), "+f"(d[10]), "+f"(d[11]), "+f"(d[12]), "+f"(d[13]), "+f"(d[14]), "+f"(d[15]),
      "+f"(d[16]), "+f"(d[17]), "+f"(d[18]), "+f"(d[19]), "+f"(d[20]), "+f"(d[21]), "+f"(d[22]), "+f"(d[23]),
      "+f"(d[24]), "+f"(d[25]), "+f"(d[26]), "+f"(d[27]), "+f"(d[28]), "+f"(d[29]), "+f"(d[30]), "+f"(d[31]),
      "+f"(d[32]), "+f"(d[33]), "+f"(d[34]), "+f"(d[35]), "+f"(d[36]), "+f"(d[37]), "+f"(d[38]), "+f"(d[39]),
      "+f"(d[40]), "+f"(d[41]), "+f"(d[42]), "+f"(d[43]), "+f"(d[44]), "+f"(d[45]), "+f"(d[46]), "+f"(d[47])
    : "l"(da), "l"(db), "r"(acc));
}
__device__ __forceinline__ void wg_ss_n64(float* d, uint64_t da, uint64_t db, int acc) {
  asm volatile("{.reg .pred p; setp.ne.b32 p, %34, 0;\n"
    "wgmma.mma_async.sync.aligned.m64n64k16.f32.bf16.bf16 {%0,%1,%2,%3,%4,%5,%6,%7,%8,%9,%10,%11,%12,%13,%14,%15,%16,%17,%18,%19,%20,%21,%22,%23,%24,%25,%26,%27,%28,%29,%30,%31}, %32, %33, p, 1, 1, 0, 1;}\n"
    : "+f"(d[0]), "+f"(d[1]), "+f"(d[2]), "+f"(d[3]), "+f"(d[4]), "+f"(d[5]), "+f"(d[6]), "+f"(d[7]),
      "+f"(d[8]), "+f"(d[9]), "+f"(d[10]), "+f"(d[11]), "+f"(d[12]), "+f"(d[13]), "+f"(d[14]), "+f"(d[15]),
      "+f"(d[16]), "+f"(d[17]), "+f"(d[18]), "+f"(d[19]), "+f"(d[20]), "+f"(d[21]), "+f"(d[22]), "+f"(d[23]),
      "+f"(d[24]), "+f"(d[25]), "+f"(d[26]), "+f"(d[27]), "+f"(d[28]), "+f"(d[29]), "+f"(d[30]), "+f"(d[31])
    : "l"(da), "l"(db), "r"(acc));
}
__device__ __forceinline__ void wg_ss_n8(float* d, uint64_t da, uint64_t db, int acc) {
  asm volatile("{.reg .pred p; setp.ne.b32 p, %6, 0;\n"
    "wgmma.mma_async.sync.aligned.m64n8k16.f32.bf16.bf16 {%0,%1,%2,%3}, %4, %5, p, 1, 1, 1, 0;}\n"
    : "+f"(d[0]), "+f"(d[1]), "+f"(d[2]), "+f"(d[3])
    : "l"(da), "l"(db), "r"(acc));
}

__device__ __forceinline__ void exp2_tile(const uint32_t* s, uint32_t* p, uint32_t cb, uint32_t cm, uint32_t ce, uint32_t c16) {
  constexpr int NS = 32 - NMU, L = 2, STEPS = NS + 3 * L + 2;
  const uint32_t* sw = s + NMU;
  uint32_t y[NS], m[NS], e[NS];
  uint16_t lo[NMU], hi[NMU];
  int issued = 0, packed = 0;
#pragma unroll
  for (int st = 0; st < STEPS; st++) {
    int tgt = ((st + 1) * NMU * 2 + NS - 1) / NS;
    if (tgt > NMU * 2) tgt = NMU * 2;
#pragma unroll
    for (int k = 0; k < 4; k++)
      if (issued < tgt) {
        int r = issued >> 1;
        if (issued & 1) asm volatile("{.reg .b16 a,b; mov.b32 {a,b}, %1; ex2.approx.f16 %0, b;}" : "=h"(hi[r]) : "r"(s[r]));
        else asm volatile("{.reg .b16 a,b; mov.b32 {a,b}, %1; ex2.approx.f16 %0, a;}" : "=h"(lo[r]) : "r"(s[r]));
        issued++;
      }
    if (st < NS) asm volatile("fma.rn.relu.f16x2 %0, %1, %2, %3;" : "=r"(y[st]) : "r"(sw[st]), "r"(0x00400040), "r"(cb));
    if (st >= L && st - L < NS) {
      if ((st - L) % SHM == SHM - 1) asm volatile("mul.lo.u32 %0, %0, 16;" : "+r"(y[st - L]));
      else asm volatile("mul.lo.u32 %0, %0, %1;" : "+r"(y[st - L]) : "r"(c16));
    }
    if (st >= 2 * L && st - 2 * L < NS) {
      int i = st - 2 * L;
      asm volatile("lop3.b32 %0, %1, 0x03ff03ff, %2, 0xEA;" : "=r"(m[i]) : "r"(y[i]), "r"(cm));
      asm volatile("lop3.b32 %0, %1, 0x7c007c00, %2, 0xEA;" : "=r"(e[i]) : "r"(y[i]), "r"(ce));
    }
    if (st >= 3 * L && st - 3 * L < NS) {
      int i = st - 3 * L;
      asm volatile("fma.rn.f16x2 %0, %1, %2, %3;" : "=r"(p[NMU + i]) : "r"(y[i]), "r"(m[i]), "r"(e[i]));
    }
    int tp = st >= 5 ? ((st - 4) * NMU * 2 + NS - 1) / NS / 2 : 0;
    if (tp > NMU || st == STEPS - 1) tp = NMU;
#pragma unroll
    for (int k = 0; k < 8; k++)
      if (packed < tp) {
        asm volatile("mov.b32 %0, {%1, %2};" : "=r"(p[packed]) : "h"(lo[packed]), "h"(hi[packed]));
        packed++;
      }
  }
}

__device__ __forceinline__ void mma16816(float* d, const uint32_t* a, uint32_t b0, uint32_t b1) {
  asm volatile("mma.sync.aligned.m16n8k16.row.col.f32.f16.f16.f32 {%0,%1,%2,%3}, {%4,%5,%6,%7}, {%8,%9}, {%0,%1,%2,%3};"
    : "+f"(d[0]), "+f"(d[1]), "+f"(d[2]), "+f"(d[3]) : "r"(a[0]), "r"(a[1]), "r"(a[2]), "r"(a[3]), "r"(b0), "r"(b1));
}
__device__ __forceinline__ uint32_t mtrans(uint32_t v) { uint32_t r; asm volatile("movmatrix.sync.aligned.m8n8.trans.b16 %0, %1;" : "=r"(r) : "r"(v)); return r; }

__device__ __noinline__ void attn_true_max(uint32_t q0, uint32_t q1, uint32_t q2, uint32_t q3, int head, uint32_t* op) {
  const int lane = threadIdx.x & 31;
  const uint32_t q[4] = {q0, q1, q2, q3};
  const uint32_t* kp = (const uint32_t*)(g_kv + head * 8192) + (lane >> 2) * 8 + (lane & 3);
  const int x0 = (lane >> 4) * 4;
  float m0 = -INFINITY, m1 = -INFINITY, l0 = 0.f, l1 = 0.f, o[2][4] = {};
#pragma unroll 1
  for (int kb = 0; kb < 64; kb++) {
    const int off = (kb >> 2) * 2048 + (kb & 3) * 256;
    uint32_t kf[8], vf[8];
#pragma unroll
    for (int i = 0; i < 8; i++) { const uint32_t* a = kp + off + (i >> 1) * 64 + (((i & 1) * 4) ^ x0); kf[i] = __ldcg(a); vf[i] = __ldcg(a + 1024); }
    float s[4][4] = {};
#pragma unroll
    for (int i = 0; i < 4; i++) mma16816(s[i], q, kf[2 * i], kf[2 * i + 1]);
    float a = m0, b = m1;
#pragma unroll
    for (int i = 0; i < 4; i++) { a = fmaxf(a, fmaxf(s[i][0], s[i][1])); b = fmaxf(b, fmaxf(s[i][2], s[i][3])); }
#pragma unroll
    for (int d = 1; d < 4; d <<= 1) { a = fmaxf(a, __shfl_xor_sync(~0u, a, d)); b = fmaxf(b, __shfl_xor_sync(~0u, b, d)); }
    const float c0 = exp2f(m0 - a), c1 = exp2f(m1 - b);
    m0 = a; m1 = b; l0 *= c0; l1 *= c1;
    uint32_t p[8];
#pragma unroll
    for (int i = 0; i < 4; i++) {
      const float e0 = exp2f(s[i][0] - a + 12.f), e1 = exp2f(s[i][1] - a + 12.f), e2 = exp2f(s[i][2] - b + 12.f), e3 = exp2f(s[i][3] - b + 12.f);
      l0 += e0 + e1; l1 += e2 + e3;
      p[2 * i] = pack_h2(e0, e1); p[2 * i + 1] = pack_h2(e2, e3);
    }
#pragma unroll
    for (int c = 0; c < 2; c++) {
      o[c][0] *= c0; o[c][1] *= c0; o[c][2] *= c1; o[c][3] *= c1;
      mma16816(o[c], p, mtrans(vf[c]), mtrans(vf[2 + c]));
      mma16816(o[c], p + 4, mtrans(vf[4 + c]), mtrans(vf[6 + c]));
    }
  }
#pragma unroll
  for (int d = 1; d < 4; d <<= 1) { l0 += __shfl_xor_sync(~0u, l0, d); l1 += __shfl_xor_sync(~0u, l1, d); }
  l0 = 1.f / l0; l1 = 1.f / l1;
  o_store(op + lane, pack_b2(o[0][0] * l0, o[0][1] * l0)); o_store(op + 64 + lane, pack_b2(o[0][2] * l1, o[0][3] * l1));
  o_store(op + 32 + lane, pack_b2(o[1][0] * l0, o[1][1] * l0)); o_store(op + 96 + lane, pack_b2(o[1][2] * l1, o[1][3] * l1));
}

__device__ __noinline__ void attn_fp32(const bf16* x, const bf16* w, int head, int row0, uint32_t* op) {
  const int lane = threadIdx.x & 31, r = lane & 15;
  float q[16], o[16], m = -INFINITY, l = 0.f;
#pragma unroll
  for (int d = 0; d < 16; d++) { q[d] = 0.f; o[d] = 0.f; }
#pragma unroll 1
  for (int k = 0; k < DM; k++) {
    const float xv = __bfloat162float(x[(row0 + r) * DM + k]);
#pragma unroll
    for (int d = 0; d < 16; d++) q[d] += xv * __bfloat162float(w[k * 3 * DM + head * 16 + d]);
  }
  const bf16* wc = w + (lane >> 4) * DM + DM + head * 16 + r;
#pragma unroll 1
  for (int key = 0; key < SEQ; key += 8) {
    float a[8] = {};
#pragma unroll 2
    for (int k = 0; k < DM; k++) {
      const float wv = __bfloat162float(wc[k * 3 * DM]);
#pragma unroll
      for (int j = 0; j < 8; j++) a[j] += wv * __bfloat162float(x[(key + j) * DM + k]);
    }
#pragma unroll
    for (int j = 0; j < 8; j++) {
      float sc = 0.f;
#pragma unroll
      for (int d = 0; d < 16; d++) sc += q[d] * __shfl_sync(~0u, a[j], d);
      sc *= 0.25f;
      const float mn = fmaxf(m, sc), c = __expf(m - mn), p = __expf(sc - mn);
      l = l * c + p; m = mn;
#pragma unroll
      for (int d = 0; d < 16; d++) o[d] = o[d] * c + p * __shfl_sync(~0u, a[j], 16 + d);
    }
  }
  l = 1.f / l;
  if (lane < 16) {
#pragma unroll
    for (int i = 0; i < 8; i++) o_store(op + (r >> 3) * 64 + (i >> 2) * 32 + (r & 7) * 4 + (i & 3), pack_b2(o[2 * i] * l, o[2 * i + 1] * l));
  }
}

__device__ __forceinline__ void ffn_cta(const Params& P, uint8_t* sm, uint32_t sb, int f, uint32_t epoch) {
  const int tid = threadIdx.x, lane = tid & 31, warp = __shfl_sync(~0u, tid >> 5, 0);
  const uint32_t bars = sb + SM_BAR;
  if (warp >= 16) {
    if (warp == 16) {
      bar_sync(1, 544);
      if (lane == 0) {
#pragma unroll 1
        for (int i = 0, s = 0, ph = 1; i < 44; i++) {
          const uint32_t bar = bars + (B_FULL + s) * 8;
          if (i >= FNS) mbar_wait(bars + (B_EMPTY + s) * 8, ph);
          if (i < 28) { mbar_expect(bar, 32768); tma2d(sb + s * FSTG, (i & 2) ? &P.wu : &P.wg, f * FSL + (i >> 2) * 64, (i & 1) * 256, bar); }
          else { mbar_expect(bar, 28672); tma2d(sb + s * FSTG, &P.wd, ((i - 28) >> 1) * 64, f * FSL + (i & 1) * 224, bar); }
          if (++s == FNS) { s = 0; ph ^= 1; }
        }
      }
    }
    return;
  }
  unsigned long long* red = (unsigned long long*)(sm + SM_RED);
  unsigned long long key[4], best[2];
#pragma unroll
  for (int i = 0; i < 4; i++) key[i] = cell_ld(g_r + i * 512 + tid);
  *(uint4*)(sm + SM_XS + tid * 16) = make_uint4(0, 0, 0, 0);
  *(uint4*)(sm + SM_HS + tid * 16) = make_uint4(0, 0, 0, 0);
#pragma unroll
  for (int i = 0; i < 4; i++) {
    uint32_t u = cell_fin(g_r + i * 512 + tid, key[i], epoch);
    u = (u & 0x80000000u) ? ~u : (u | 0x80000000u);
    key[i] = ((unsigned long long)u << 32) | (uint32_t)(SEQ - 1 - (i * 512 + tid));
  }
#pragma unroll
  for (int r = 0; r < 2; r++) {
    unsigned long long b = 0;
#pragma unroll
    for (int i = 0; i < 4; i++) if (!(r == 1 && key[i] == best[0]) && key[i] > b) b = key[i];
#pragma unroll
    for (int d = 16; d; d >>= 1) { unsigned long long o = __shfl_xor_sync(~0u, b, d); b = o > b ? o : b; }
    if (lane == 0) red[r * 16 + warp] = b;
    bar_sync(1 + r, r ? 512 : 544);
#pragma unroll
    for (int i = 0; i < 16; i++) b = red[r * 16 + i] > b ? red[r * 16 + i] : b;
    best[r] = b;
  }
  if (warp >= 4) return;
  const int i0 = SEQ - 1 - (int)(uint32_t)best[0], i1 = SEQ - 1 - (int)(uint32_t)best[1];
  *(uint4*)(sm + SM_XS + (tid & 63) * 128 + (tid >> 6) * 16) = __ldg((const uint4*)(P.px + (tid < 64 ? i0 : i1) * DM) + (tid & 63));
  float rs[2];
#pragma unroll
  for (int t = 0; t < 2; t++) {
    const uint32_t u = (uint32_t)(best[t] >> 32);
    rs[t] = sigmoidf(__uint_as_float((u & 0x80000000u) ? (u & 0x7fffffffu) : ~u));
  }
  fence_async();
  bar_sync(3, 128);
  const int row = warp * 16 + (lane >> 2);
  float acc[4], gate[4];
#pragma unroll 1
  for (int i = 0, s = 0, ph = 0; i < 44; i++) {
    mbar_wait(bars + (B_FULL + s) * 8, ph);
    const uint64_t da = make_desc(sb + s * FSTG, 8192, 1024, 1);
    const uint64_t db = make_desc(i < 28 ? sb + SM_XS + (i & 1) * 4096 : sb + SM_HS + (i & 1) * 3584, 128, 256, 0);
    wg_fence();
#pragma unroll
    for (int ks = 0; ks < 14; ks++) wg_ss_n8(acc, da + ks * 128, db + ks * 16, (i & 1) | ks);
    wg_commit();
    if (i < 28) { wg_fence(); wg_ss_n8(acc, da + 14 * 128, db + 14 * 16, 1); wg_ss_n8(acc, da + 15 * 128, db + 15 * 16, 1); wg_commit(); }
    wg_wait<0>();
    pin<4>(acc);
    if (lane == 0) mbar_arrive(bars + (B_EMPTY + s) * 8);
    if (++s == FNS) { s = 0; ph ^= 1; }
    if (i >= 28) {
      if ((i & 1) && (lane & 3) == 0) {
#pragma unroll
        for (int j = 0; j < 4; j++) g_y[(f * 2 + (j & 1)) * DM + ((i - 28) >> 1) * 64 + row + (j >> 1) * 8] = acc[j] * rs[j & 1];
      }
    } else if ((i & 3) == 1) {
#pragma unroll
      for (int j = 0; j < 4; j++) gate[j] = acc[j] * sigmoidf(acc[j]);
    } else if ((i & 3) == 3) {
      if ((lane & 3) == 0) {
#pragma unroll
        for (int j = 0; j < 4; j++)
          *(bf16*)(sm + SM_HS + ((i >> 2) * 8 + warp * 2 + (j >> 1)) * 128 + (j & 1) * 16 + (lane >> 2) * 2) = __float2bfloat16(gate[j] * acc[j]);
      }
      if (i == 27) { fence_async(); bar_sync(3, 128); }
    }
  }
  bar_sync(3, 128);
  if (tid == 0) {
    __threadfence();
    cell_set(g_fy + f, (uint32_t)i0 | ((uint32_t)i1 << 16), epoch);
    g_epoch[NMAIN + f] = epoch;
  }
  TSTAMP(7, tid == 0)
}

__device__ __forceinline__ uint32_t max_norm2(const float* k) {
  float n0 = k[0] * k[0] + k[1] * k[1] + k[4] * k[4] + k[5] * k[5], n1 = k[2] * k[2] + k[3] * k[3] + k[6] * k[6] + k[7] * k[7];
  const bool odd = threadIdx.x & 1;
  n0 = (odd ? n1 : n0) + __shfl_xor_sync(~0u, odd ? n0 : n1, 1);
  n0 += __shfl_xor_sync(~0u, n0, 2);
  return __reduce_max_sync(~0u, __float_as_uint(n0) & 0x7fffffffu);
}

__global__ void __launch_bounds__(NTHR, 1) fused_kernel(const __grid_constant__ Params P) {
  extern __shared__ uint8_t smem_raw[];
  const uint32_t sraw = (uint32_t)__cvta_generic_to_shared(smem_raw);
  const uint32_t sb = (sraw + 1023) & ~1023u;
  uint8_t* sm = smem_raw + (sb - sraw);
  const uint32_t bars = sb + SM_BAR;
  const int tid = threadIdx.x, lane = tid & 31, warp = __shfl_sync(~0u, tid >> 5, 0), wg = warp >> 2, wi = warp & 3;
  const int cta = blockIdx.x, tq = cta >> 4, hp = cta & 15;
  TSTAMP(0, tid == 0)
  if (warp == 0) {
    if (elect()) {
      asm volatile("prefetch.tensormap [%0];" ::"l"(&P.x) : "memory");
#pragma unroll
      for (int c = 0; c < B_EMPTY; c++) mbar_init(bars + (B_FULL + c) * 8, 1);
      fence_async();
      if (cta < NMAIN) {
#pragma unroll
        for (int c = 0; c < NSTAGE; c++) {
          const uint32_t st = sb + (c < 3 ? c + 2 : c - 3) * STG, bar = bars + (B_FULL + c) * 8;
          mbar_expect(bar, STG);
          tma3d(st + STG_A, &P.w, hp * 32, c * 64, 0, bar);
          tma2d(st, &P.x, c * 64, tq * 256, bar);
        }
      }
    }
  } else if (warp == 1) {
    if (elect()) {
#pragma unroll
      for (int c = B_EMPTY; c < B_N; c++)
        mbar_init(bars + c * 8, c < B_KV ? (cta < NMAIN ? 16 : 4) : c < B_FREE0 ? (0x44421 >> (4 * (c - B_KV))) & 15 : c < B_WO ? 16 : c < B_OB ? 1 : 2);
      fence_async();
    }
  } else if (warp == 17) {
    *(uint4*)(sm + SM_ONE + lane * 16) = make_uint4(0x3c003c00u, 0x3c003c00u, 0x3c003c00u, 0x3c003c00u);
    if (lane == 0) *(uint4*)(sm + SM_STAT) = make_uint4(0, 0, 0, 0);
    if (lane == 1) *(uint4*)(sm + SM_STAT + 32) = make_uint4(0x039a039au, 0x38003800u, 0x000b000bu, 16);
    if (lane < 4) *(uint2*)(sm + SM_STAT + 48 + lane * 8) = make_uint2(4 + lane, 4 + ((lane + 1) & 3));
    fence_async();
  }
  const uint32_t epoch = __reduce_max_sync(~0u, __ldcg(g_epoch + cta) + 1);
  __syncthreads();
  if (cta >= NMAIN) { ffn_cta(P, sm, sb, cta - NMAIN, epoch); return; }
  const int rt3 = tq * 4 + (hp >> 2), cs = hp & 3;

  if (wg == 4) {
    if (wi != 0) {
      const uint4* wr = (const uint4*)P.pwr; const uint4* gw = (const uint4*)P.pgw;
      const int t0 = cta * 16 + (wi - 1) * 5;
      uint4 xv[6][2], a[2], b[2];
#pragma unroll
      for (int t = 0; t < 6; t++)
#pragma unroll
        for (int j = 0; j < 2; j++) xv[t][j] = __ldg((const uint4*)(P.px + (t0 + t) * DM) + j * 32 + lane);
#pragma unroll
      for (int j = 0; j < 2; j++) { a[j] = __ldg(wr + j * 32 + lane); b[j] = __ldg(gw + j * 32 + lane); }
      for (int i = tid - 544; i < 512; i += 96) g_o[((tq * 4 + (i >> 7)) * 2 + 1) * 2048 + hp * 128 + (i & 127)] = make_uint4(0, 0, 0, 0);
#pragma unroll
      for (int t = 0; t < 6; t++) {
        float r = 0.f, g = 0.f;
#pragma unroll
        for (int j = 0; j < 2; j++) {
          const uint32_t xu[4] = {xv[t][j].x, xv[t][j].y, xv[t][j].z, xv[t][j].w};
          const uint32_t au[4] = {a[j].x, a[j].y, a[j].z, a[j].w}, bu[4] = {b[j].x, b[j].y, b[j].z, b[j].w};
#pragma unroll
          for (int i = 0; i < 4; i++) {
            r += b_lo(xu[i]) * b_lo(au[i]) + b_hi(xu[i]) * b_hi(au[i]);
            g += b_lo(xu[i]) * b_lo(bu[i]) + b_hi(xu[i]) * b_hi(bu[i]);
          }
        }
#pragma unroll
        for (int d = 16; d; d >>= 1) { r += __shfl_xor_sync(~0u, r, d); g += __shfl_xor_sync(~0u, g, d); }
        if (lane == 0 && (t < 5 || wi == 3)) { cell_set(g_r + t0 + t, __float_as_uint(r), epoch); cell_set(g_g + t0 + t, __float_as_uint(sigmoidf(g)), epoch); }
      }
    }
    asm volatile("setmaxnreg.dec.sync.aligned.u32 32;");
    if (wi >= 2) { bar_arrive(1, NTHR); return; }
    if (wi == 1) {
      bar_sync(1, NTHR);
      if (elect()) {
        bulk_out(g_kv + (hp * 32 + tq * 2) * 512, sb + 2 * SLOT, 2 * SLOT);
        bulk_out(g_kv + (hp * 32 + 16 + tq * 2) * 512, sb, 2 * SLOT);
        asm volatile("cp.async.bulk.commit_group;" ::: "memory");
        const uint4 st = *(const uint4*)(sm + SM_STAT);
        asm volatile("cp.async.bulk.wait_group 0;" ::: "memory");
        fence_async_g();
        asm volatile("st.relaxed.gpu.global.v4.u32 [%0], {%1, %2, %3, %2};"
          ::"l"(g_f1 + hp * 8 + tq), "r"(min((st.x >> 16) + 1, 0x7fffu) | (st.y & 0xffff0000u)), "r"(epoch),
            "r"(min((st.z >> 16) + 1, 0x7fffu) | (st.w & 0xffff0000u)) : "memory");
        TSTAMP(4, true)
      }
      return;
    }
    if (elect()) {
#pragma unroll 1
      for (int kc = NSTAGE; kc < 8; kc++) {
        const uint32_t st = sb + (kc - 3) * STG, bar = bars + (B_FULL + kc - NSTAGE) * 8;
        mbar_wait(bars + (B_EMPTY + kc - NSTAGE) * 8, 0);
        mbar_expect(bar, STG);
        tma3d(st + STG_A, &P.w, hp * 32, kc * 64, 0, bar);
        tma2d(st, &P.x, kc * 64, tq * 256, bar);
      }
      asm volatile("cp.async.bulk.prefetch.L2.global [%0], %1;" ::"l"(P.pwo + cta * 2048), "r"(4096) : "memory");
    }
    __syncwarp();
    bar_sync(1, NTHR);
    {
      const uint4* fp = g_f1 + hp * 8 + ((tq + lane) & 7);
      uint32_t sa, sc, rdy = 1, got = 1, c = 0;
#pragma unroll 1
      for (int pos = 2; pos < 16; pos++) {
        if (pos == 5) mbar_wait(bars + (B_KV + 1) * 8, 0);
        if (pos == 9) {
#pragma unroll
          for (int d = 1; d < 8; d <<= 1) { sa = __vmaxu2(sa, __shfl_xor_sync(~0u, sa, d)); sc = __vmaxu2(sc, __shfl_xor_sync(~0u, sc, d)); }
          if (lane == 0) { *(uint2*)(sm + SM_STAT + 16) = make_uint2(sa, sc); mbar_arrive(bars + (B_KV + 3) * 8); }
          mbar_wait(bars + (B_KV + 2) * 8, 0);
          got = 1;
        }
        if (pos == 12) mbar_wait(bars + B_FREE0 * 8, 0);
        while ((pos == 8 ? rdy != 0xff : !(rdy & ~got)) && ++c < SPIN_LIMIT) {
          uint32_t e0, e1;
          asm volatile("ld.acquire.gpu.global.v4.u32 {%0, %1, %2, %3}, [%4];" : "=r"(sa), "=r"(e0), "=r"(sc), "=r"(e1) : "l"(fp) : "memory");
          rdy = __ballot_sync(~0u, e0 == epoch && e1 == epoch) & 0xff;
          fence_async_g();
        }
        const int i = __ffs(rdy & ~got) - 1;
        got |= 1u << i;
        const uint32_t bar = bars + (B_KV + (pos < 3 ? 0 : pos < 5 ? 1 : pos < 9 ? 2 : pos < 12 ? 3 : 4)) * 8;
        if (elect()) {
          mbar_expect(bar, 2 * SLOT);
          bulk(sb + (pos < 12 ? pos : pos - 12) * 2 * SLOT, g_kv + (hp * 16 + (pos < 9 ? 0 : 8) + ((tq + i) & 7)) * 1024, 2 * SLOT, bar);
        }
        TSTAMP(5, lane == 0 && pos == 2)
      }
    }
    __syncwarp();
    mbar_wait(bars + B_ORDY * 8, 0);
    if (lane == 0) asm volatile("st.release.gpu.global.u32 [%0], %1;" ::"l"(g_f2 + cta), "r"(epoch) : "memory");
    mbar_wait(bars + B_FREE1 * 8, 0);
    if (lane == 0) {
      mbar_expect(bars + B_WO * 8, 131072);
#pragma unroll
      for (int j = 0; j < 4; j++) tma2d(sb + SM_WO + j * 32768, &P.wo, cs * 128 + (j >> 1) * 64, (j & 1) * 256, bars + B_WO * 8);
    }
    __syncwarp();
    uint32_t v, c = 0;
    do {
      asm volatile("ld.acquire.gpu.global.u32 %0, [%1];" : "=r"(v) : "l"(g_f2 + tq * 16 + (lane & 15)) : "memory");
      if (++c > SPIN_LIMIT) break;
    } while (!__all_sync(~0u, v == epoch));
    if (lane == 0) {
      fence_async_g();
      mbar_expect(bars + B_OA * 8, 32768);
      bulk(sb + SM_OA, g_o + rt3 * 4096, 32768, bars + B_OA * 8);
    }
    return;
  }

  uint32_t q[4], q2[4], qn[2];
  {
    float acc[48];
#pragma unroll 1
    for (int kc = 0; kc < 8; kc++) {
      const int s = kc >= NSTAGE ? kc - NSTAGE : kc;
      const uint32_t st = sb + (kc < 3 ? kc + 2 : kc - 3) * STG;
      mbar_wait(bars + (B_FULL + s) * 8, kc >= NSTAGE);
      TSTAMP(1, tid == 0 && kc == 0)
      const uint64_t da = make_desc(st + wg * 8192, 16, 1024, 1), db = make_desc(st + STG_A, 4096, 512, 2);
      wg_fence();
#pragma unroll
      for (int ks = 0; ks < 4; ks++) wg_ss_n96(acc, da + ks * 2, db + ks * 64, kc | ks);
      wg_commit();
      wg_wait<1>();
      if (kc >= 1 && kc <= 4 && lane == 0) mbar_arrive(bars + (B_EMPTY + kc - 1) * 8);
    }
    mbar_wait(bars + (B_EMPTY + 3) * 8, 0);
    wg_wait<0>();
    pin<48>(acc);
    asm volatile("setmaxnreg.inc.sync.aligned.u32 112;");
    TSTAMP(2, tid == 0)
    const uint32_t ka = sb + (wg >> 1) * SLOT + (warp & 7) * 512 + (lane & 15) * 32 + (((lane >> 4) ^ (lane >> 2)) & 1) * 16;
#pragma unroll
    for (int hb = 1; hb >= 0; hb--) {
      uint32_t kk[4], vv[4];
#pragma unroll
      for (int i = 0; i < 4; i++) {
        kk[i] = pack_h2(acc[16 + hb * 8 + 2 * i], acc[17 + hb * 8 + 2 * i]);
        vv[i] = pack_h2(acc[32 + hb * 8 + 2 * i], acc[33 + hb * 8 + 2 * i]);
      }
      stsm4(ka + (1 - hb) * 2 * SLOT, kk);
      stsm4(ka + (1 - hb) * 2 * SLOT + 4096, vv);
    }
    fence_async();
#pragma unroll
    for (int hb = 0; hb < 2; hb++) {
      const float* v = acc + 32 + hb * 8;
      uint32_t vm = 0;
#pragma unroll
      for (int i = 0; i < 8; i++) vm = max(vm, __float_as_uint(v[i]) & 0x7fffffffu);
      vm = __reduce_max_sync(~0u, vm);
      const uint32_t kn = max_norm2(acc + 16 + hb * 8);
      if (lane < 2) atomicMax((uint32_t*)(sm + SM_STAT + hb * 8 + lane * 4), lane ? vm : kn);
      qn[hb] = max_norm2(acc + hb * 8);
    }
#pragma unroll
    for (int i = 0; i < 4; i++) { q2[i] = pack_h2(acc[2 * i] * QS, acc[2 * i + 1] * QS); q[i] = pack_h2(acc[8 + 2 * i] * QS, acc[9 + 2 * i] * QS); }
  }
  bar_sync(1, NTHR);
  TSTAMP(3, tid == 0)

  uint32_t* const op = (uint32_t*)(g_o + (tq * 4 + wg) * 4096 + hp * 128 + wi * 32);
  uint32_t redo = 0;
  uint8_t* const park = sm + SM_OA + tid * 16;
  *(uint4*)park = make_uint4(q2[0], q2[1], q2[2], q2[3]);
  *(uint4*)(park + 8192) = make_uint4(q[0], q[1], q[2], q[3]);
  {
    uint32_t cb, cm, ce, c16;
    asm volatile("ld.volatile.shared.v4.u32 {%0, %1, %2, %3}, [%4];" : "=r"(cb), "=r"(cm), "=r"(ce), "=r"(c16) : "r"(sb + SM_STAT + 32));
    constexpr long long VK = 32 - (32 << 16), VT = 512 - (512 << 16);
    uint64_t dv = make_desc(sb + 4096, SM_ONE - 4096, 256, 3);
    uint32_t bs, ba;
    asm volatile("ld.volatile.shared.v2.u32 {%0, %1}, [%2];" : "=r"(bs), "=r"(ba) : "r"(sb + SM_STAT + 48 + wg * 8));
    uint32_t s[32], p[32], o[12];
#pragma unroll
    for (int i = 0; i < 12; i++) o[i] = 0;
    pin<12>(o);
    wg_fence(); wg_qk(s, q, dv - 256); wg_commit();
    if (wg == 3) bar_arrive(4, 256);
    wg_wait<0>();
#pragma unroll 1
    for (int seg = 0;; seg++) {
      pin<32>(s); pin<12>(o);
      if (seg == 1 || seg == 6) {
        const uint4 t = *(const uint4*)(park + (seg & 4) * 2048);
        q[0] = t.x; q[1] = t.y; q[2] = t.z; q[3] = t.w;
      }
      if (seg == 2) {
#pragma unroll
        for (int i = 0; i < 6; i++) { const __half2 t = __hadd2(*(__half2*)&o[i], *(__half2*)&o[6 + i]); o[i] = *(const uint32_t*)&t; }
        *(uint4*)(park + 16384) = make_uint4(o[0], o[1], o[2], o[3]);
        *(uint2*)(park + 24576) = make_uint2(o[4], o[5]);
#pragma unroll
        for (int i = 0; i < 12; i++) o[i] = 0;
      } else if (seg == 9) {
        if (lane == 0) mbar_arrive(bars + B_FREE1 * 8);
        dv -= NSLOT * VT;
      } else if (seg == 7 || seg == 10) {
        const int hb = seg == 10;
        if (lane == 0) mbar_arrive(bars + (hb ? B_DONE : B_FREE0) * 8);
        uint32_t* dst = op + hb * 8192 + lane;
        TSTAMP(tid ? 16 : 10 + hb * 2, tid == 0 || tid == 384)
        float f[10];
#pragma unroll
        for (int i = 0; i < 4; i++) { f[2 * i] = h_lo(o[i]) + h_lo(o[6 + i]); f[2 * i + 1] = h_hi(o[i]) + h_hi(o[6 + i]); }
        f[8] = h_lo(o[4]) + h_lo(o[10]); f[9] = h_lo(o[5]) + h_lo(o[11]);
        const uint32_t st = *(const uint32_t*)(sm + SM_STAT + 16 + hb * 4);
        const float kn2 = b_lo(st), vm = b_hi(st);
        const float qn2 = __uint_as_float(hb ? qn[1] : qn[0]) * (QS * QS);
        const float tot = ((f[0] + f[1]) + (f[2] + f[3])) + ((f[4] + f[5]) + (f[6] + f[7])) + (f[8] + f[9]);
        const bool in_range = kn2 <= 1.6e7f && vm >= 6.2e-5f && vm <= 6.0e4f && qn2 <= 1.6e7f;
        const bool safe = in_range && qn2 * kn2 <= 289.f && f[8] >= 64.f && f[9] >= 64.f && fabsf(tot) <= 1e30f;
        if (__all_sync(~0u, safe)) {
          const float i0 = 1.f / f[8], i1 = 1.f / f[9];
          o_store(dst, pack_b2(f[0] * i0, f[1] * i0)); o_store(dst + 64, pack_b2(f[2] * i1, f[3] * i1));
          o_store(dst + 32, pack_b2(f[4] * i0, f[5] * i0)); o_store(dst + 96, pack_b2(f[6] * i1, f[7] * i1));
          __syncwarp();
          if (!hb && lane == 0) mbar_arrive(bars + B_ORDY * 8);
        } else {
          redo |= (in_range ? 1 : 3) << (hb * 2);
          if (!hb) ((uint4*)op)[lane] = *(const uint4*)park;
        }
        if (hb) break;
        const uint4 t = *(const uint4*)(park + 16384);
        const uint2 u = *(const uint2*)(park + 24576);
        o[0] = t.x; o[1] = t.y; o[2] = t.z; o[3] = t.w; o[4] = u.x; o[5] = u.y;
#pragma unroll
        for (int i = 6; i < 12; i++) o[i] = 0;
      } else if (seg >= 3) {
        TSTAMP(11, tid == 0 && seg == 3)
        TSTAMP(14, tid == 0 && seg == 6)
        mbar_wait(bars + (B_KV + (seg == 8 ? 4 : seg - 3)) * 8, 0);
        TSTAMP(6, tid == 0 && seg == 3)
        TSTAMP(13, tid == 0 && seg == 5)
      }
      pin<12>(o);
      int n = (int)(0x8151842111ull >> (4 * seg)) & 15;
      const long long dk = seg == 8 ? 256 - NSLOT * 512 : 256;
#pragma unroll 1
      do {
        exp2_tile(s, p, cb, cm, ce, c16);
        wg_fence();
        wg_pv(o, p, dv);
        bar_sync(bs, 256);
#pragma unroll
        for (int j = 1; j < 8; j++) wg_pv(o + (j & 1) * 6, p + j * 4, dv + j * VK);
        wg_qk(s, q, dv + dk);
        dv += VT;
        wg_commit();
        bar_arrive(ba, 256);
        wg_wait<0>();
        pin<32>(s);
      } while (--n);
    }
  }
  TSTAMP(17, tid == 384)
  if (wg == 0) bar_sync(4, 256);
  if (redo) {
#pragma unroll 1
    for (int hb = 0; hb < 2; hb++) {
      const uint32_t m = (redo >> (hb * 2)) & 3;
      if (m == 1) {
        const uint4 t = hb ? make_uint4(q[0], q[1], q[2], q[3]) : ((const uint4*)op)[lane];
        attn_true_max(t.x, t.y, t.z, t.w, hp * 2 + hb, op + hb * 8192);
      }
      if (m == 3) attn_fp32(P.px, P.pw, hp * 2 + hb, tq * 256 + warp * 16, op + hb * 8192);
      __syncwarp();
      if (m && !hb && lane == 0) mbar_arrive(bars + B_ORDY * 8);
    }
  }

  if (wg >= 2) {
    const uint4* src = g_o + rt3 * 4096 + 2048 + (warp - 8) * 256 + lane;
    uint4 v[8];
    mbar_wait(bars + B_OA * 8, 0);
    uint32_t todo = 0xff;
    for (uint32_t c = 0; todo; c++) {
      if (c > SPIN_LIMIT) break;
#pragma unroll
      for (int i = 0; i < 8; i++)
        if (todo >> i & 1) asm volatile("ld.relaxed.gpu.global.v4.u32 {%0, %1, %2, %3}, [%4];" : "=r"(v[i].x), "=r"(v[i].y), "=r"(v[i].z), "=r"(v[i].w) : "l"(src + i * 32) : "memory");
#pragma unroll
      for (int i = 0; i < 8; i++)
        if (__all_sync(~0u, min(min(v[i].x, v[i].y), min(v[i].z, v[i].w)) != 0)) todo &= ~(1u << i);
      TSTAMP(18, tid == 384 && c == 0)
    }
    mbar_wait(bars + B_DONE * 8, 0);
#pragma unroll
    for (int i = 0; i < 8; i++) *(uint4*)(sm + SM_OB + (warp - 8) * 4096 + i * 512 + lane * 16) = v[i];
    fence_async();
    __syncwarp();
    if (lane == 0) mbar_arrive(bars + (B_OB + ((warp - 8) >> 1)) * 8);
    TSTAMP(tid == 256 ? 8 : 25, tid == 256 || tid == 384)
  } else {
    const int r0 = rt3 * 64 + wi * 16 + (lane >> 2), c0 = cs * 128 + wg * 64 + (lane & 3) * 2;
    uint32_t xr[16];
#pragma unroll
    for (int i = 0; i < 16; i++) xr[i] = __ldg((const uint32_t*)(P.px + (r0 + (i & 1) * 8) * DM + c0 + (i >> 1) * 8));
    const unsigned long long u0 = cell_ld(g_g + r0), u1 = cell_ld(g_g + r0 + 8), u2 = cell_ld(g_fy + (lane & 3));
    float pre[32], acc[32];
    const uint64_t db = make_desc(sb + SM_WO + wg * 65536, 8192, 1024, 1);
    mbar_wait(bars + B_WO * 8, 0);
    mbar_wait(bars + B_OA * 8, 0);
    wg_fence();
#pragma unroll
    for (int ks = 0; ks < 16; ks++) wg_ss_n64(acc, make_desc(sb + SM_OA, 128, 256, 0) + ks * 128, db + ks * 256, ks);
    wg_commit();
    TSTAMP(19, tid == 0)
    const float g0 = __uint_as_float(cell_fin(g_g + r0, u0, epoch)), g1 = __uint_as_float(cell_fin(g_g + r0 + 8, u1, epoch));
    const uint32_t idx = cell_fin(g_fy + (lane & 3), u2, epoch);
#pragma unroll
    for (int i = 0; i < 16; i++) { pre[2 * i] = b_lo(xr[i]); pre[2 * i + 1] = b_hi(xr[i]); }
#pragma unroll
    for (int t = 0; t < 2; t++) {
      const int d = (int)((idx >> (16 * t)) & 0xffff) - r0;
      if (d == 0 || d == 8) {
        __threadfence();
#pragma unroll 1
        for (int f = 0; f < NFFN; f++) {
#pragma unroll
          for (int nb = 0; nb < 8; nb++) {
            const float2 y = __ldcg((const float2*)(g_y + (f * 2 + t) * DM + c0 + nb * 8));
            if (d == 0) { pre[nb * 4] += y.x; pre[nb * 4 + 1] += y.y; } else { pre[nb * 4 + 2] += y.x; pre[nb * 4 + 3] += y.y; }
          }
        }
      }
    }
    __syncwarp();
#pragma unroll
    for (int i = 0; i < 32; i++) pre[i] *= 1.f - ((i & 2) ? g1 : g0);
    pin<32>(pre);
    TSTAMP(20, tid == 0)
#pragma unroll
    for (int c = 0; c < 4; c++) {
      mbar_wait(bars + (B_OB + c) * 8, 0);
      TSTAMP(21 + c, tid == 0)
      wg_fence();
#pragma unroll
      for (int ks = c * 4; ks < c * 4 + 4; ks++) wg_ss_n64(acc, make_desc(sb + SM_OB, 128, 256, 0) + ks * 128, db + ks * 256 + 128, 1);
      wg_commit();
    }
    wg_wait<0>();
    pin<32>(acc);
    TSTAMP(9, tid == 0)
    const uint32_t stg = sb + SM_OUT + warp * 2048;
    const int row = lane & 15;
#pragma unroll
    for (int j = 0; j < 4; j++) {
      uint32_t r[4];
#pragma unroll
      for (int i = 0; i < 4; i++) {
        const int k = j * 8 + i * 2; const float g = (i & 1) ? g1 : g0;
        r[i] = pack_b2(fmaf(g, acc[k], pre[k]), fmaf(g, acc[k + 1], pre[k + 1]));
      }
      stsm4(stg + row * 128 + (((j * 2 + (lane >> 4)) ^ (row & 7)) << 4), r);
    }
    fence_async();
    __syncwarp();
    if (lane == 0) {
      asm volatile("cp.async.bulk.tensor.2d.global.shared::cta.bulk_group [%0, {%2, %3}], [%1];"
        ::"l"(&P.out), "r"(stg), "r"(cs * 128 + wg * 64), "r"(rt3 * 64 + wi * 16) : "memory");
      asm volatile("cp.async.bulk.commit_group;" ::: "memory");
      asm volatile("cp.async.bulk.wait_group.read 0;" ::: "memory");
    }
    if (tid == 0) g_epoch[cta] = epoch;
    TSTAMP(7, tid == 0)
  }
}

typedef CUresult (*EncodeFn)(CUtensorMap*, CUtensorMapDataType, cuuint32_t, void*, const cuuint64_t*, const cuuint64_t*,
                             const cuuint32_t*, const cuuint32_t*, CUtensorMapInterleave, CUtensorMapSwizzle,
                             CUtensorMapL2promotion, CUtensorMapFloatOOBfill);
static void make_map(EncodeFn enc, CUtensorMap* m, const void* p, int cols, int rows, int box_rows) {
  cuuint64_t dim[2] = {(cuuint64_t)cols, (cuuint64_t)rows}, str[1] = {(cuuint64_t)cols * 2};
  cuuint32_t box[2] = {64, (cuuint32_t)box_rows}, es[2] = {1, 1};
  enc(m, CU_TENSOR_MAP_DATA_TYPE_BFLOAT16, 2, (void*)p, dim, str, box, es, CU_TENSOR_MAP_INTERLEAVE_NONE,
      CU_TENSOR_MAP_SWIZZLE_128B, CU_TENSOR_MAP_L2_PROMOTION_L2_128B, CU_TENSOR_MAP_FLOAT_OOB_FILL_NONE);
}

extern "C" void kernel_launch(void* const* d_in, const int* in_sizes, int n_in, void* d_out, int out_size) {
  static EncodeFn enc = nullptr;
  if (!enc) {
    void* fn = nullptr; cudaDriverEntryPointQueryResult qr;
    cudaGetDriverEntryPoint("cuTensorMapEncodeTiled", &fn, cudaEnableDefault, &qr);
    enc = (EncodeFn)fn;
    cudaFuncSetAttribute(fused_kernel, cudaFuncAttributeMaxDynamicSharedMemorySize, SM_TOTAL);
  }
  Params P;
  make_map(enc, &P.x, d_in[0], DM, SEQ, 256);
  make_map(enc, &P.wo, d_in[2], DM, DM, 256);
  make_map(enc, &P.out, d_out, DM, SEQ, 16);
  make_map(enc, &P.wg, d_in[5], FF, DM, 256);
  make_map(enc, &P.wu, d_in[6], FF, DM, 256);
  make_map(enc, &P.wd, d_in[7], DM, FF, 224);
  {
    cuuint64_t dim[3] = {DM, DM, 3}, str[2] = {3 * DM * 2, DM * 2};
    cuuint32_t box[3] = {32, 64, 3}, es[3] = {1, 1, 1};
    enc(&P.w, CU_TENSOR_MAP_DATA_TYPE_BFLOAT16, 3, d_in[1], dim, str, box, es, CU_TENSOR_MAP_INTERLEAVE_NONE,
        CU_TENSOR_MAP_SWIZZLE_64B, CU_TENSOR_MAP_L2_PROMOTION_L2_128B, CU_TENSOR_MAP_FLOAT_OOB_FILL_NONE);
  }
  P.px = (const bf16*)d_in[0]; P.pw = (const bf16*)d_in[1]; P.pwo = (const bf16*)d_in[2];
  P.pwr = (const bf16*)d_in[4]; P.pgw = (const bf16*)d_in[8];
  fused_kernel<<<NCTA, NTHR, SM_TOTAL, cudaStreamPerThread>>>(P);
}
```

```cpp
#include <cuda_runtime.h>
#include <cuda.h>
#include <cuda_bf16.h>
#include <cuda_fp16.h>
#include <stdint.h>

typedef __nv_bfloat16 bf16;

constexpr int SEQ = 2048, DM = 512, NH = 32, FF = 1792;
constexpr int NMAIN = 128, NFFN = 4, NCTA = NMAIN + NFFN, NTHR = 640;
constexpr float QS = 0.25f * 1.4426950408889634f;
constexpr int FSL = FF / NFFN;
#define NMU 10
#define LAG 3
#define QKO 65536
#define SHM 4

constexpr int NSTAGE = 5, STG_A = 32768, STG = STG_A + 12288;
constexpr int SLOT = 8192, NSLOT = 18, SM_PARK = NSLOT * SLOT;
constexpr int SM_ONE = 28 * SLOT, SM_BAR = SM_ONE + 512, SM_STAT = SM_BAR + 256, SM_G = SM_STAT + 128, SM_TAB = SM_G + 512, SM_ORD = SM_TAB + 256;
constexpr int SM_WO3 = 0, SM_OA = 4 * SLOT, SM_OB = 8 * SLOT, SM_WO = 14 * SLOT, SM_X = 26 * SLOT;
constexpr int SM_TOTAL = SM_ORD + 128 + 1024;
constexpr int FSTG = 32768, FNS = 6, SM_XS = FNS * FSTG, SM_HS = SM_XS + 8192, SM_RED = SM_HS + 8192;
constexpr int B_FULL = 0, B_EMPTY = 6, B_KV = 12, B_FREE0 = 17, B_FREE2 = 18, B_ORDY = 19, B_FREE1 = 20, B_X = 21, B_Y = 22, B_OA = 23, B_WO = 24, B_N = 25;

__device__ uint4 g_kv[NH * 16 * 512];
__device__ uint4 g_o[32 * NH * 128];
__device__ uint4 g_f1[NMAIN];
__device__ uint32_t g_f2[NMAIN];
__device__ uint2 g_r[SEQ], g_g[SEQ];
__device__ float g_y[NFFN * 2 * DM];
__device__ uint2 g_fy[NFFN];
__device__ uint32_t g_epoch[NCTA];
#define TSTAMPD(k, i, cond)
#define TSTAMP(i, cond) TSTAMPD(i, i, cond)

struct Params {
  CUtensorMap x, w, wo, xr, wg, wu, wd;
  const bf16 *px, *pw, *pwo, *pwr, *pgw;
  bf16* pout;
};

constexpr uint32_t SPIN_LIMIT = 1u << 21;
__device__ __forceinline__ void wg_fence() { asm volatile("wgmma.fence.sync.aligned;" ::: "memory"); }
__device__ __forceinline__ void wg_commit() { asm volatile("wgmma.commit_group.sync.aligned;" ::: "memory"); }
template <int N> __device__ __forceinline__ void wg_wait() { asm volatile("wgmma.wait_group.sync.aligned %0;" ::"n"(N) : "memory"); }
template <int N> __device__ __forceinline__ void pin(uint32_t* s) {
#pragma unroll
  for (int i = 0; i < N; i++) asm volatile("" : "+r"(s[i])::"memory");
}
template <int N> __device__ __forceinline__ void pin(float* s) {
#pragma unroll
  for (int i = 0; i < N; i++) asm volatile("" : "+f"(s[i])::"memory");
}
__device__ __forceinline__ bool elect() {
  uint32_t p;
  asm volatile("{.reg .pred p; elect.sync _|p, 0xffffffff; selp.u32 %0, 1, 0, p;}" : "=r"(p));
  return p;
}
__device__ __forceinline__ void mbar_init(uint32_t bar, uint32_t cnt) { asm volatile("mbarrier.init.shared::cta.b64 [%0], %1;" ::"r"(bar), "r"(cnt) : "memory"); }
__device__ __forceinline__ void mbar_expect(uint32_t bar, uint32_t bytes) { asm volatile("mbarrier.arrive.expect_tx.shared::cta.b64 _, [%0], %1;" ::"r"(bar), "r"(bytes) : "memory"); }
__device__ __forceinline__ void mbar_arrive(uint32_t bar) { asm volatile("mbarrier.arrive.shared::cta.b64 _, [%0];" ::"r"(bar) : "memory"); }
__device__ __forceinline__ void mbar_wait(uint32_t bar, uint32_t parity) {
  asm volatile("{.reg .pred p; .reg .b32 c;\n"
    "mbarrier.try_wait.parity.shared::cta.b64 p, [%0], %1;\n"
    "@p bra.uni DONE;\n"
    "mov.b32 c, 0;\n"
    "LOOP: mbarrier.try_wait.parity.shared::cta.b64 p, [%0], %1, 1000;\n"
    "@p bra.uni DONE;\n"
    "add.u32 c, c, 1;\n"
    "setp.lt.u32 p, c, %2;\n"
    "@p bra.uni LOOP;\n"
    "DONE: }" ::"r"(bar), "r"(parity), "n"(SPIN_LIMIT) : "memory");
}
__device__ __forceinline__ void tma2d(uint32_t dst, const CUtensorMap* m, int c0, int c1, uint32_t bar) {
  asm volatile("cp.async.bulk.tensor.2d.shared::cluster.global.mbarrier::complete_tx::bytes [%0], [%1, {%3, %4}], [%2];"
    ::"r"(dst), "l"(m), "r"(bar), "r"(c0), "r"(c1) : "memory");
}
__device__ __forceinline__ void tma3d(uint32_t dst, const CUtensorMap* m, int c0, int c1, int c2, uint32_t bar) {
  asm volatile("cp.async.bulk.tensor.3d.shared::cluster.global.mbarrier::complete_tx::bytes [%0], [%1, {%3, %4, %5}], [%2];"
    ::"r"(dst), "l"(m), "r"(bar), "r"(c0), "r"(c1), "r"(c2) : "memory");
}
__device__ __forceinline__ void bulk(uint32_t dst, const void* src, uint32_t bytes, uint32_t bar) {
  asm volatile("cp.async.bulk.shared::cluster.global.mbarrier::complete_tx::bytes [%0], [%1], %2, [%3];"
    ::"r"(dst), "l"(src), "r"(bytes), "r"(bar) : "memory");
}
__device__ __forceinline__ void bulk_out(void* dst, uint32_t src, uint32_t bytes) {
  asm volatile("cp.async.bulk.global.shared::cta.bulk_group [%0], [%1], %2;" ::"l"(dst), "r"(src), "r"(bytes) : "memory");
}
__device__ __forceinline__ void fence_async() { asm volatile("fence.proxy.async.shared::cta;" ::: "memory"); }
__device__ __forceinline__ void fence_async_g() { asm volatile("fence.proxy.async.global;" ::: "memory"); }
__device__ __forceinline__ void bar_sync(int id, int n) { asm volatile("bar.sync %0, %1;" ::"r"(id), "r"(n) : "memory"); }
__device__ __forceinline__ void bar_arrive(int id, int n) { asm volatile("bar.arrive %0, %1;" ::"r"(id), "r"(n) : "memory"); }
__device__ __forceinline__ void stsm4(uint32_t a, const uint32_t* r) {
  asm volatile("stmatrix.sync.aligned.m8n8.x4.shared.b16 [%0], {%1, %2, %3, %4};" ::"r"(a), "r"(r[0]), "r"(r[1]), "r"(r[2]), "r"(r[3]) : "memory");
}
__device__ __forceinline__ void ldsm4(uint32_t* r, uint32_t a) {
  asm volatile("ldmatrix.sync.aligned.m8n8.x4.shared.b16 {%0, %1, %2, %3}, [%4];" : "=r"(r[0]), "=r"(r[1]), "=r"(r[2]), "=r"(r[3]) : "r"(a) : "memory");
}
__device__ __forceinline__ void sts128(uint32_t a, const uint32_t* r) { asm volatile("st.shared.v4.u32 [%0], {%1, %2, %3, %4};" ::"r"(a), "r"(r[0]), "r"(r[1]), "r"(r[2]), "r"(r[3]) : "memory"); }
__device__ __forceinline__ void sts64(uint32_t a, const uint32_t* r) { asm volatile("st.shared.v2.u32 [%0], {%1, %2};" ::"r"(a), "r"(r[0]), "r"(r[1]) : "memory"); }
__device__ __forceinline__ void lds128(uint32_t* r, uint32_t a) { asm volatile("ld.shared.v4.u32 {%0, %1, %2, %3}, [%4];" : "=r"(r[0]), "=r"(r[1]), "=r"(r[2]), "=r"(r[3]) : "r"(a) : "memory"); }
__device__ __forceinline__ void lds64(uint32_t* r, uint32_t a) { asm volatile("ld.shared.v2.u32 {%0, %1}, [%2];" : "=r"(r[0]), "=r"(r[1]) : "r"(a) : "memory"); }
__device__ __forceinline__ void cell_set(uint2* p, uint32_t v, uint32_t e) { asm volatile("st.relaxed.gpu.global.v2.u32 [%0], {%1, %2};" ::"l"(p), "r"(v), "r"(e) : "memory"); }
__device__ __forceinline__ unsigned long long cell_ld(const uint2* p) {
  unsigned long long v;
  asm volatile("ld.relaxed.gpu.global.u64 %0, [%1];" : "=l"(v) : "l"(p) : "memory");
  return v;
}
__device__ __forceinline__ uint32_t cell_fin(const uint2* p, unsigned long long v, uint32_t e) {
  for (uint32_t c = 0; !__all_sync(~0u, (uint32_t)(v >> 32) == e); c++) {
    if (c > SPIN_LIMIT) break;
    v = cell_ld(p);
  }
  return (uint32_t)v;
}
__device__ __forceinline__ uint64_t make_desc(uint32_t addr, uint32_t lbo, uint32_t sbo, uint32_t swz) {
  return (uint64_t)((addr & 0x3FFFF) >> 4) | ((uint64_t)(lbo >> 4) << 16) | ((uint64_t)(sbo >> 4) << 32) | ((uint64_t)swz << 62);
}
constexpr long long VK = 32 - (32 << 16), VT = 512 - (512 << 16);
__device__ __forceinline__ uint64_t kv_desc(uint32_t sb) { return make_desc(sb, SM_ONE, 256, 3); }
__device__ __forceinline__ void desc_step(uint64_t& d, int c) { asm("{.reg .b32 l, h; mov.b64 {l, h}, %0; add.u32 l, l, %1; mov.b64 %0, {l, h};}" : "+l"(d) : "r"(c)); }
__device__ __forceinline__ uint32_t pack_h2(float lo, float hi) { uint32_t r; asm("cvt.rn.f16x2.f32 %0, %1, %2;" : "=r"(r) : "f"(hi), "f"(lo)); return r; }
__device__ __forceinline__ uint32_t pack_b2(float lo, float hi) { uint32_t r; asm("cvt.rn.bf16x2.f32 %0, %1, %2;" : "=r"(r) : "f"(hi), "f"(lo)); return r; }
__device__ __forceinline__ float b_lo(uint32_t v) { return __uint_as_float(v << 16); }
__device__ __forceinline__ float b_hi(uint32_t v) { return __uint_as_float(v & 0xffff0000u); }
__device__ __forceinline__ float h_lo(uint32_t v) { return __half2float(__ushort_as_half((unsigned short)(v & 0xffff))); }
__device__ __forceinline__ float h_hi(uint32_t v) { return __half2float(__ushort_as_half((unsigned short)(v >> 16))); }
__device__ __forceinline__ float sigmoidf(float v) { return 1.f / (1.f + __expf(-v)); }
__device__ __forceinline__ void o_store(uint32_t* p, uint32_t v) {
  asm volatile("st.relaxed.gpu.global.u32 [%0], %1;" ::"l"(p), "r"(max(v, 1u)) : "memory");
}

__device__ __forceinline__ void wg_qk(uint32_t* d, const uint32_t* a, uint64_t desc) {
  asm volatile("{.reg .pred p; setp.ne.b32 p, 0, 0;\n"
    "wgmma.mma_async.sync.aligned.m64n128k16.f16.f16.f16 {%0,%1,%2,%3,%4,%5,%6,%7,%8,%9,%10,%11,%12,%13,%14,%15,%16,%17,%18,%19,%20,%21,%22,%23,%24,%25,%26,%27,%28,%29,%30,%31}, {%32,%33,%34,%35}, %36, p, 1, 1, 0;}\n"
    : "=r"(d[0]), "=r"(d[1]), "=r"(d[2]), "=r"(d[3]), "=r"(d[4]), "=r"(d[5]), "=r"(d[6]), "=r"(d[7]),
      "=r"(d[8]), "=r"(d[9]), "=r"(d[10]), "=r"(d[11]), "=r"(d[12]), "=r"(d[13]), "=r"(d[14]), "=r"(d[15]),
      "=r"(d[16]), "=r"(d[17]), "=r"(d[18]), "=r"(d[19]), "=r"(d[20]), "=r"(d[21]), "=r"(d[22]), "=r"(d[23]),
      "=r"(d[24]), "=r"(d[25]), "=r"(d[26]), "=r"(d[27]), "=r"(d[28]), "=r"(d[29]), "=r"(d[30]), "=r"(d[31])
    : "r"(a[0]), "r"(a[1]), "r"(a[2]), "r"(a[3]), "l"(desc));
}
__device__ __forceinline__ void wg_pv(uint32_t* d, const uint32_t* a, uint64_t desc) {
  asm volatile("{.reg .pred p; setp.eq.b32 p, 0, 0;\n"
    "wgmma.mma_async.sync.aligned.m64n24k16.f16.f16.f16 {%0,%1,%2,%3,%4,%5}, {%6,%7,%8,%9}, %10, p, 1, 1, 1;}\n"
    : "+r"(d[0]), "+r"(d[1]), "+r"(d[2]), "+r"(d[3]), "+r"(d[4]), "+r"(d[5])
    : "r"(a[0]), "r"(a[1]), "r"(a[2]), "r"(a[3]), "l"(desc));
}
__device__ __forceinline__ void wg_ss_n96(float* d, uint64_t da, uint64_t db, int acc) {
  asm volatile("{.reg .pred p; setp.ne.b32 p, %50, 0;\n"
    "wgmma.mma_async.sync.aligned.m64n96k16.f32.bf16.bf16 {%0,%1,%2,%3,%4,%5,%6,%7,%8,%9,%10,%11,%12,%13,%14,%15,%16,%17,%18,%19,%20,%21,%22,%23,%24,%25,%26,%27,%28,%29,%30,%31,%32,%33,%34,%35,%36,%37,%38,%39,%40,%41,%42,%43,%44,%45,%46,%47}, %48, %49, p, 1, 1, 0, 1;}\n"
    : "+f"(d[0]), "+f"(d[1]), "+f"(d[2]), "+f"(d[3]), "+f"(d[4]), "+f"(d[5]), "+f"(d[6]), "+f"(d[7]),
      "+f"(d[8]), "+f"(d[9]), "+f"(d[10]), "+f"(d[11]), "+f"(d[12]), "+f"(d[13]), "+f"(d[14]), "+f"(d[15]),
      "+f"(d[16]), "+f"(d[17]), "+f"(d[18]), "+f"(d[19]), "+f"(d[20]), "+f"(d[21]), "+f"(d[22]), "+f"(d[23]),
      "+f"(d[24]), "+f"(d[25]), "+f"(d[26]), "+f"(d[27]), "+f"(d[28]), "+f"(d[29]), "+f"(d[30]), "+f"(d[31]),
      "+f"(d[32]), "+f"(d[33]), "+f"(d[34]), "+f"(d[35]), "+f"(d[36]), "+f"(d[37]), "+f"(d[38]), "+f"(d[39]),
      "+f"(d[40]), "+f"(d[41]), "+f"(d[42]), "+f"(d[43]), "+f"(d[44]), "+f"(d[45]), "+f"(d[46]), "+f"(d[47])
    : "l"(da), "l"(db), "r"(acc));
}
__device__ __forceinline__ void wg_ss_n128(float* d, uint64_t da, uint64_t db, int acc) {
  asm volatile("{.reg .pred p; setp.ne.b32 p, %66, 0;\n"
    "wgmma.mma_async.sync.aligned.m64n128k16.f32.bf16.bf16 {%0,%1,%2,%3,%4,%5,%6,%7,%8,%9,%10,%11,%12,%13,%14,%15,%16,%17,%18,%19,%20,%21,%22,%23,%24,%25,%26,%27,%28,%29,%30,%31,%32,%33,%34,%35,%36,%37,%38,%39,%40,%41,%42,%43,%44,%45,%46,%47,%48,%49,%50,%51,%52,%53,%54,%55,%56,%57,%58,%59,%60,%61,%62,%63}, %64, %65, p, 1, 1, 0, 1;}\n"
    : "+f"(d[0]), "+f"(d[1]), "+f"(d[2]), "+f"(d[3]), "+f"(d[4]), "+f"(d[5]), "+f"(d[6]), "+f"(d[7]),
      "+f"(d[8]), "+f"(d[9]), "+f"(d[10]), "+f"(d[11]), "+f"(d[12]), "+f"(d[13]), "+f"(d[14]), "+f"(d[15]),
      "+f"(d[16]), "+f"(d[17]), "+f"(d[18]), "+f"(d[19]), "+f"(d[20]), "+f"(d[21]), "+f"(d[22]), "+f"(d[23]),
      "+f"(d[24]), "+f"(d[25]), "+f"(d[26]), "+f"(d[27]), "+f"(d[28]), "+f"(d[29]), "+f"(d[30]), "+f"(d[31]),
      "+f"(d[32]), "+f"(d[33]), "+f"(d[34]), "+f"(d[35]), "+f"(d[36]), "+f"(d[37]), "+f"(d[38]), "+f"(d[39]),
      "+f"(d[40]), "+f"(d[41]), "+f"(d[42]), "+f"(d[43]), "+f"(d[44]), "+f"(d[45]), "+f"(d[46]), "+f"(d[47]),
      "+f"(d[48]), "+f"(d[49]), "+f"(d[50]), "+f"(d[51]), "+f"(d[52]), "+f"(d[53]), "+f"(d[54]), "+f"(d[55]),
      "+f"(d[56]), "+f"(d[57]), "+f"(d[58]), "+f"(d[59]), "+f"(d[60]), "+f"(d[61]), "+f"(d[62]), "+f"(d[63])
    : "l"(da), "l"(db), "r"(acc));
}
__device__ __forceinline__ void wg_ss_n8(float* d, uint64_t da, uint64_t db, int acc) {
  asm volatile("{.reg .pred p; setp.ne.b32 p, %6, 0;\n"
    "wgmma.mma_async.sync.aligned.m64n8k16.f32.bf16.bf16 {%0,%1,%2,%3}, %4, %5, p, 1, 1, 1, 0;}\n"
    : "+f"(d[0]), "+f"(d[1]), "+f"(d[2]), "+f"(d[3])
    : "l"(da), "l"(db), "r"(acc));
}

__device__ __forceinline__ void exp2_tile(const uint32_t* s, uint32_t* p, uint32_t cb, uint32_t cm, uint32_t ce, uint32_t c16) {
  constexpr int NS = 32 - NMU, L = LAG, STEPS = NS + 3 * L + 2;
  const uint32_t* sw = s + NMU;
  uint32_t y[NS], m[NS], e[NS];
  uint16_t lo[NMU], hi[NMU];
  int issued = 0, packed = 0;
#pragma unroll
  for (int st = 0; st < STEPS; st++) {
    int tgt = ((st + 1) * NMU * 2 + NS - 1) / NS;
    if (tgt > NMU * 2) tgt = NMU * 2;
#pragma unroll
    for (int k = 0; k < 4; k++)
      if (issued < tgt) {
        int r = issued >> 1;
        if (issued & 1) asm volatile("{.reg .b16 a,b; mov.b32 {a,b}, %1; ex2.approx.f16 %0, b;}" : "=h"(hi[r]) : "r"(s[r]));
        else asm volatile("{.reg .b16 a,b; mov.b32 {a,b}, %1; ex2.approx.f16 %0, a;}" : "=h"(lo[r]) : "r"(s[r]));
        issued++;
      }
    if (st < NS) asm volatile("fma.rn.relu.f16x2 %0, %1, %2, %3;" : "=r"(y[st]) : "r"(sw[st]), "r"(0x00400040), "r"(cb));
    if (st >= L && st - L < NS) {
      if ((st - L) % SHM == SHM - 1) asm volatile("mul.lo.u32 %0, %0, 16;" : "+r"(y[st - L]));
      else asm volatile("mul.lo.u32 %0, %0, %1;" : "+r"(y[st - L]) : "r"(c16));
    }
    if (st >= 2 * L && st - 2 * L < NS) {
      int i = st - 2 * L;
      asm volatile("lop3.b32 %0, %1, 0x03ff03ff, %2, 0xEA;" : "=r"(m[i]) : "r"(y[i]), "r"(cm));
      asm volatile("lop3.b32 %0, %1, 0x7c007c00, %2, 0xEA;" : "=r"(e[i]) : "r"(y[i]), "r"(ce));
    }
    if (st >= 3 * L && st - 3 * L < NS) {
      int i = st - 3 * L;
      asm volatile("fma.rn.f16x2 %0, %1, %2, %3;" : "=r"(p[NMU + i]) : "r"(y[i]), "r"(m[i]), "r"(e[i]));
    }
    int tp = st >= 5 ? ((st - 4) * NMU * 2 + NS - 1) / NS / 2 : 0;
    if (tp > NMU || st == STEPS - 1) tp = NMU;
#pragma unroll
    for (int k = 0; k < 8; k++)
      if (packed < tp) {
        asm volatile("mov.b32 %0, {%1, %2};" : "=r"(p[packed]) : "h"(lo[packed]), "h"(hi[packed]));
        packed++;
      }
  }
}

__device__ __forceinline__ void mma16816(float* d, const uint32_t* a, uint32_t b0, uint32_t b1) {
  asm volatile("mma.sync.aligned.m16n8k16.row.col.f32.f16.f16.f32 {%0,%1,%2,%3}, {%4,%5,%6,%7}, {%8,%9}, {%0,%1,%2,%3};"
    : "+f"(d[0]), "+f"(d[1]), "+f"(d[2]), "+f"(d[3]) : "r"(a[0]), "r"(a[1]), "r"(a[2]), "r"(a[3]), "r"(b0), "r"(b1));
}
__device__ __forceinline__ uint32_t mtrans(uint32_t v) { uint32_t r; asm volatile("movmatrix.sync.aligned.m8n8.trans.b16 %0, %1;" : "=r"(r) : "r"(v)); return r; }

__device__ __noinline__ void attn_true_max(uint32_t q0, uint32_t q1, uint32_t q2, uint32_t q3, int head, uint32_t* op) {
  const int lane = threadIdx.x & 31;
  const uint32_t q[4] = {q0, q1, q2, q3};
  const uint32_t* kp = (const uint32_t*)(g_kv + head * 8192) + (lane >> 2) * 8 + (lane & 3);
  const int x0 = (lane >> 4) * 4;
  float m0 = -INFINITY, m1 = -INFINITY, l0 = 0.f, l1 = 0.f, o[2][4] = {};
#pragma unroll 1
  for (int kb = 0; kb < 64; kb++) {
    const int off = (kb >> 2) * 2048 + (kb & 3) * 256;
    uint32_t kf[8], vf[8];
#pragma unroll
    for (int i = 0; i < 8; i++) { const uint32_t* a = kp + off + (i >> 1) * 64 + (((i & 1) * 4) ^ x0); kf[i] = __ldcg(a); vf[i] = __ldcg(a + 1024); }
    float s[4][4] = {};
#pragma unroll
    for (int i = 0; i < 4; i++) mma16816(s[i], q, kf[2 * i], kf[2 * i + 1]);
    float a = m0, b = m1;
#pragma unroll
    for (int i = 0; i < 4; i++) { a = fmaxf(a, fmaxf(s[i][0], s[i][1])); b = fmaxf(b, fmaxf(s[i][2], s[i][3])); }
#pragma unroll
    for (int d = 1; d < 4; d <<= 1) { a = fmaxf(a, __shfl_xor_sync(~0u, a, d)); b = fmaxf(b, __shfl_xor_sync(~0u, b, d)); }
    const float c0 = exp2f(m0 - a), c1 = exp2f(m1 - b);
    m0 = a; m1 = b; l0 *= c0; l1 *= c1;
    uint32_t p[8];
#pragma unroll
    for (int i = 0; i < 4; i++) {
      const float e0 = exp2f(s[i][0] - a + 12.f), e1 = exp2f(s[i][1] - a + 12.f), e2 = exp2f(s[i][2] - b + 12.f), e3 = exp2f(s[i][3] - b + 12.f);
      l0 += e0 + e1; l1 += e2 + e3;
      p[2 * i] = pack_h2(e0, e1); p[2 * i + 1] = pack_h2(e2, e3);
    }
#pragma unroll
    for (int c = 0; c < 2; c++) {
      o[c][0] *= c0; o[c][1] *= c0; o[c][2] *= c1; o[c][3] *= c1;
      mma16816(o[c], p, mtrans(vf[c]), mtrans(vf[2 + c]));
      mma16816(o[c], p + 4, mtrans(vf[4 + c]), mtrans(vf[6 + c]));
    }
  }
#pragma unroll
  for (int d = 1; d < 4; d <<= 1) { l0 += __shfl_xor_sync(~0u, l0, d); l1 += __shfl_xor_sync(~0u, l1, d); }
  l0 = 1.f / l0; l1 = 1.f / l1;
  o_store(op + lane, pack_b2(o[0][0] * l0, o[0][1] * l0)); o_store(op + 64 + lane, pack_b2(o[0][2] * l1, o[0][3] * l1));
  o_store(op + 32 + lane, pack_b2(o[1][0] * l0, o[1][1] * l0)); o_store(op + 96 + lane, pack_b2(o[1][2] * l1, o[1][3] * l1));
}

__device__ __noinline__ void attn_fp32(const bf16* x, const bf16* w, int head, int row0, uint32_t* op) {
  const int lane = threadIdx.x & 31, r = lane & 15;
  float q[16], o[16], m = -INFINITY, l = 0.f;
#pragma unroll
  for (int d = 0; d < 16; d++) { q[d] = 0.f; o[d] = 0.f; }
#pragma unroll 1
  for (int k = 0; k < DM; k++) {
    const float xv = __bfloat162float(x[(row0 + r) * DM + k]);
#pragma unroll
    for (int d = 0; d < 16; d++) q[d] += xv * __bfloat162float(w[k * 3 * DM + head * 16 + d]);
  }
  const bf16* wc = w + (lane >> 4) * DM + DM + head * 16 + r;
#pragma unroll 1
  for (int key = 0; key < SEQ; key += 8) {
    float a[8] = {};
#pragma unroll 2
    for (int k = 0; k < DM; k++) {
      const float wv = __bfloat162float(wc[k * 3 * DM]);
#pragma unroll
      for (int j = 0; j < 8; j++) a[j] += wv * __bfloat162float(x[(key + j) * DM + k]);
    }
#pragma unroll
    for (int j = 0; j < 8; j++) {
      float sc = 0.f;
#pragma unroll
      for (int d = 0; d < 16; d++) sc += q[d] * __shfl_sync(~0u, a[j], d);
      sc *= 0.25f;
      const float mn = fmaxf(m, sc), c = __expf(m - mn), p = __expf(sc - mn);
      l = l * c + p; m = mn;
#pragma unroll
      for (int d = 0; d < 16; d++) o[d] = o[d] * c + p * __shfl_sync(~0u, a[j], 16 + d);
    }
  }
  l = 1.f / l;
  if (lane < 16) {
#pragma unroll
    for (int i = 0; i < 8; i++) o_store(op + (r >> 3) * 64 + (i >> 2) * 32 + (r & 7) * 4 + (i & 3), pack_b2(o[2 * i] * l, o[2 * i + 1] * l));
  }
}

__device__ __forceinline__ void ffn_cta(const Params& P, uint8_t* sm, uint32_t sb, int f, uint32_t epoch) {
  const int tid = threadIdx.x, lane = tid & 31, warp = __shfl_sync(~0u, tid >> 5, 0);
  const uint32_t bars = sb + SM_BAR;
  if (warp >= 16) {
    if (warp == 16) {
      bar_sync(1, 544);
      if (lane == 0) {
#pragma unroll 1
        for (int i = 0, s = 0, ph = 1; i < 44; i++) {
          const uint32_t bar = bars + (B_FULL + s) * 8;
          if (i >= FNS) mbar_wait(bars + (B_EMPTY + s) * 8, ph);
          if (i < 28) { mbar_expect(bar, 32768); tma2d(sb + s * FSTG, (i & 2) ? &P.wu : &P.wg, f * FSL + (i >> 2) * 64, (i & 1) * 256, bar); }
          else { mbar_expect(bar, 28672); tma2d(sb + s * FSTG, &P.wd, ((i - 28) >> 1) * 64, f * FSL + (i & 1) * 224, bar); }
          if (++s == FNS) { s = 0; ph ^= 1; }
        }
      }
    }
    return;
  }
  unsigned long long* red = (unsigned long long*)(sm + SM_RED);
  unsigned long long key[4], best[2];
#pragma unroll
  for (int i = 0; i < 4; i++) key[i] = cell_ld(g_r + i * 512 + tid);
  *(uint4*)(sm + SM_XS + tid * 16) = make_uint4(0, 0, 0, 0);
  *(uint4*)(sm + SM_HS + tid * 16) = make_uint4(0, 0, 0, 0);
#pragma unroll
  for (int i = 0; i < 4; i++) {
    uint32_t u = cell_fin(g_r + i * 512 + tid, key[i], epoch);
    u = (u & 0x80000000u) ? ~u : (u | 0x80000000u);
    key[i] = ((unsigned long long)u << 32) | (uint32_t)(SEQ - 1 - (i * 512 + tid));
  }
#pragma unroll
  for (int r = 0; r < 2; r++) {
    unsigned long long b = 0;
#pragma unroll
    for (int i = 0; i < 4; i++) if (!(r == 1 && key[i] == best[0]) && key[i] > b) b = key[i];
#pragma unroll
    for (int d = 16; d; d >>= 1) { unsigned long long o = __shfl_xor_sync(~0u, b, d); b = o > b ? o : b; }
    if (lane == 0) red[r * 16 + warp] = b;
    bar_sync(1 + r, r ? 512 : 544);
#pragma unroll
    for (int i = 0; i < 16; i++) b = red[r * 16 + i] > b ? red[r * 16 + i] : b;
    best[r] = b;
  }
  if (warp >= 4) return;
  const int i0 = SEQ - 1 - (int)(uint32_t)best[0], i1 = SEQ - 1 - (int)(uint32_t)best[1];
  *(uint4*)(sm + SM_XS + (tid & 63) * 128 + (tid >> 6) * 16) = __ldg((const uint4*)(P.px + (tid < 64 ? i0 : i1) * DM) + (tid & 63));
  float rs[2];
#pragma unroll
  for (int t = 0; t < 2; t++) {
    const uint32_t u = (uint32_t)(best[t] >> 32);
    rs[t] = sigmoidf(__uint_as_float((u & 0x80000000u) ? (u & 0x7fffffffu) : ~u));
  }
  fence_async();
  bar_sync(3, 128);
  const int row = warp * 16 + (lane >> 2);
  float acc[4], gate[4];
#pragma unroll 1
  for (int i = 0, s = 0, ph = 0; i < 44; i++) {
    mbar_wait(bars + (B_FULL + s) * 8, ph);
    const uint64_t da = make_desc(sb + s * FSTG, 8192, 1024, 1);
    const uint64_t db = make_desc(i < 28 ? sb + SM_XS + (i & 1) * 4096 : sb + SM_HS + (i & 1) * 3584, 128, 256, 0);
    wg_fence();
#pragma unroll
    for (int ks = 0; ks < 14; ks++) wg_ss_n8(acc, da + ks * 128, db + ks * 16, (i & 1) | ks);
    wg_commit();
    if (i < 28) { wg_fence(); wg_ss_n8(acc, da + 14 * 128, db + 14 * 16, 1); wg_ss_n8(acc, da + 15 * 128, db + 15 * 16, 1); wg_commit(); }
    wg_wait<0>();
    pin<4>(acc);
    if (lane == 0) mbar_arrive(bars + (B_EMPTY + s) * 8);
    if (++s == FNS) { s = 0; ph ^= 1; }
    if (i >= 28) {
      if ((i & 1) && (lane & 3) == 0) {
#pragma unroll
        for (int j = 0; j < 4; j++) g_y[(f * 2 + (j & 1)) * DM + ((i - 28) >> 1) * 64 + row + (j >> 1) * 8] = acc[j] * rs[j & 1];
      }
    } else if ((i & 3) == 1) {
#pragma unroll
      for (int j = 0; j < 4; j++) gate[j] = acc[j] * sigmoidf(acc[j]);
    } else if ((i & 3) == 3) {
      if ((lane & 3) == 0) {
#pragma unroll
        for (int j = 0; j < 4; j++)
          *(bf16*)(sm + SM_HS + ((i >> 2) * 8 + warp * 2 + (j >> 1)) * 128 + (j & 1) * 16 + (lane >> 2) * 2) = __float2bfloat16(gate[j] * acc[j]);
      }
      if (i == 27) { fence_async(); bar_sync(3, 128); }
    }
  }
  bar_sync(3, 128);
  if (tid == 0) {
    __threadfence();
    cell_set(g_fy + f, (uint32_t)i0 | ((uint32_t)i1 << 16), epoch);
    g_epoch[NMAIN + f] = epoch;
  }
  TSTAMP(7, tid == 0)
}

__device__ __forceinline__ uint32_t max_norm2(const float* k) {
  float n0 = k[0] * k[0] + k[1] * k[1] + k[4] * k[4] + k[5] * k[5], n1 = k[2] * k[2] + k[3] * k[3] + k[6] * k[6] + k[7] * k[7];
  const bool odd = threadIdx.x & 1;
  n0 = (odd ? n1 : n0) + __shfl_xor_sync(~0u, odd ? n0 : n1, 1);
  n0 += __shfl_xor_sync(~0u, n0, 2);
  return __reduce_max_sync(~0u, __float_as_uint(n0) & 0x7fffffffu);
}

__device__ __forceinline__ bool kv_in_range(uint32_t st) { return b_lo(st) <= 1.6e7f && b_hi(st) >= 6.2e-5f && b_hi(st) <= 6.0e4f; }
__device__ __forceinline__ uint32_t q_limit(uint32_t st) {
  return kv_in_range(st) ? __float_as_uint(fminf(__fdividef(289.f, b_lo(st)), 1.6e7f) * (1.f / (QS * QS))) + 1 : 0;
}

__global__ void __launch_bounds__(NTHR, 1) fused_kernel(const __grid_constant__ Params P) {
  extern __shared__ uint8_t smem_raw[];
  const uint32_t sraw = (uint32_t)__cvta_generic_to_shared(smem_raw);
  const uint32_t sb = (sraw + 1023) & ~1023u;
  uint8_t* sm = smem_raw + (sb - sraw);
  const uint32_t bars = sb + SM_BAR;
  const int tid = threadIdx.x, lane = tid & 31, warp = __shfl_sync(~0u, tid >> 5, 0), wg = warp >> 2, wi = warp & 3;
  const int cta = blockIdx.x, tq = cta >> 4, hp = cta & 15;
  TSTAMP(0, tid == 0)
  uint32_t last = 0;
  if (wg == 4 || cta >= NMAIN) asm volatile("ld.relaxed.gpu.global.u32 %0, [%1];" : "=r"(last) : "l"(g_epoch + cta) : "memory");
  if (warp == 0) {
    if (elect()) {
      asm volatile("prefetch.tensormap [%0];" ::"l"(&P.x) : "memory");
#pragma unroll
      for (int c = 0; c < B_EMPTY; c++) mbar_init(bars + (B_FULL + c) * 8, 1);
      fence_async();
      if (cta < NMAIN) {
#pragma unroll
        for (int c = 0; c < NSTAGE; c++) {
          const uint32_t st = sb + (c < 3 ? c + 2 : c - 3) * STG, bar = bars + (B_FULL + c) * 8;
          mbar_expect(bar, STG);
          tma3d(st + STG_A, &P.w, hp * 32, c * 64, 0, bar);
          tma2d(st, &P.x, c * 64, tq * 256, bar);
          if (c == 0) { TSTAMP(27, true) }
        }
        TSTAMP(28, true)
      }
    }
  } else if (warp == 1) {
    if (elect()) {
#pragma unroll
      for (int c = B_EMPTY; c < B_N; c++)
        mbar_init(bars + c * 8, c < B_KV ? (cta < NMAIN ? 16 : 4) : c < B_ORDY ? (0x4453421 >> (4 * (c - B_KV))) & 15 : c < B_X ? 16 : c < B_WO ? 1 : 2);
      fence_async();
    }
  } else if (warp == 17) {
    *(uint4*)(sm + SM_ONE + lane * 16) = make_uint4(0x3c003c00u, 0x3c003c00u, 0x3c003c00u, 0x3c003c00u);
    if (lane == 0 || lane == 5) *(uint4*)(sm + SM_STAT + lane * 16) = make_uint4(0, 0, 0, 0);
    *(uint32_t*)(sm + SM_ORD + lane * 4) = 0;
    if (lane == 1) *(uint4*)(sm + SM_STAT + 32) = make_uint4(0x039a039au, 0x38003800u, 0x000b000bu, 16);
    if (lane < 4) *(uint2*)(sm + SM_STAT + 48 + lane * 8) = make_uint2(4 + lane, 4 + ((lane + 1) & 3));
    const uint32_t e = (lane < 8 ? 0x0e071209050302ull : lane < 24 ? 0x0e1202ull : 0x0e09120902ull) >> (lane & 7) * 8 & 255;
    const uint32_t b = (lane < 8 ? 0x0f000e0d0c00ull : lane < 24 ? 0ull : 0x12001100ull) >> (lane & 7) * 8 & 255;
    *(uint2*)(sm + SM_TAB + lane * 8) = make_uint2((uint32_t)kv_desc(sb) + e * (uint32_t)VT, b ? bars + b * 8 : 0);
    fence_async();
  }
  __syncthreads();
  TSTAMP(29, tid == 0)
  if (cta >= NMAIN) { ffn_cta(P, sm, sb, cta - NMAIN, last + 1); return; }
  const int rt3 = tq * 4 + (hp >> 2), cs = hp & 3;

  if (wg == 4) {
    const uint32_t epoch = last + 1;
    if (wi != 0) {
      const uint4* wr = (const uint4*)P.pwr; const uint4* gw = (const uint4*)P.pgw;
      const int t0 = cta * 16 + (wi - 1) * 5;
      uint4 xv[6][2], a[2], b[2];
#pragma unroll
      for (int t = 0; t < 6; t++)
#pragma unroll
        for (int j = 0; j < 2; j++) xv[t][j] = __ldg((const uint4*)(P.px + (t0 + t) * DM) + j * 32 + lane);
#pragma unroll
      for (int j = 0; j < 2; j++) { a[j] = __ldg(wr + j * 32 + lane); b[j] = __ldg(gw + j * 32 + lane); }
      for (int i = tid - 544; i < 512; i += 96) g_o[((tq * 4 + (i >> 7)) * 2 + 1) * 2048 + hp * 128 + (i & 127)] = make_uint4(0, 0, 0, 0);
#pragma unroll
      for (int t = 0; t < 6; t++) {
        float r = 0.f, g = 0.f;
#pragma unroll
        for (int j = 0; j < 2; j++) {
          const uint32_t xu[4] = {xv[t][j].x, xv[t][j].y, xv[t][j].z, xv[t][j].w};
          const uint32_t au[4] = {a[j].x, a[j].y, a[j].z, a[j].w}, bu[4] = {b[j].x, b[j].y, b[j].z, b[j].w};
#pragma unroll
          for (int i = 0; i < 4; i++) {
            r += b_lo(xu[i]) * b_lo(au[i]) + b_hi(xu[i]) * b_hi(au[i]);
            g += b_lo(xu[i]) * b_lo(bu[i]) + b_hi(xu[i]) * b_hi(bu[i]);
          }
        }
#pragma unroll
        for (int d = 16; d; d >>= 1) { r += __shfl_xor_sync(~0u, r, d); g += __shfl_xor_sync(~0u, g, d); }
        if (lane == 0 && (t < 5 || wi == 3)) { cell_set(g_r + t0 + t, __float_as_uint(r), epoch); cell_set(g_g + t0 + t, __float_as_uint(sigmoidf(g)), epoch); }
      }
    }
    asm volatile("setmaxnreg.dec.sync.aligned.u32 32;");
    if (wi >= 2) { bar_arrive(1, NTHR); return; }
    if (wi == 1) {
      bar_sync(1, NTHR);
      if (elect()) {
        bulk_out(g_kv + (hp * 32 + tq * 2) * 512, sb + 2 * SLOT, 2 * SLOT);
        bulk_out(g_kv + (hp * 32 + 16 + tq * 2) * 512, sb, 2 * SLOT);
        asm volatile("cp.async.bulk.commit_group;" ::: "memory");
        const uint4 st = *(const uint4*)(sm + SM_STAT);
        asm volatile("cp.async.bulk.wait_group 0;" ::: "memory");
        fence_async_g();
        asm volatile("st.relaxed.gpu.global.v4.u32 [%0], {%1, %2, %3, %2};"
          ::"l"(g_f1 + hp * 8 + tq), "r"(min((st.x >> 16) + 1, 0x7fffu) | (st.y & 0xffff0000u)), "r"(epoch),
            "r"(min((st.z >> 16) + 1, 0x7fffu) | (st.w & 0xffff0000u)) : "memory");
        TSTAMP(4, true)
      }
      return;
    }
    if (elect()) {
#pragma unroll 1
      for (int kc = NSTAGE; kc < 8; kc++) {
        const uint32_t st = sb + (kc - 3) * STG, bar = bars + (B_FULL + kc - NSTAGE) * 8;
        mbar_wait(bars + (B_EMPTY + kc - NSTAGE) * 8, 0);
        mbar_expect(bar, STG);
        tma3d(st + STG_A, &P.w, hp * 32, kc * 64, 0, bar);
        tma2d(st, &P.x, kc * 64, tq * 256, bar);
      }
      asm volatile("cp.async.bulk.prefetch.L2.global [%0], %1;" ::"l"(P.pwo + cta * 2048), "r"(4096) : "memory");
    }
    __syncwarp();
    bar_sync(1, NTHR);
    {
      const uint4* fp = g_f1 + hp * 8 + ((tq + lane) & 7);
      uint32_t sa, sc, rdy = 1, got = 1, c = 0;
#pragma unroll 1
      for (int pos = 2; pos < 16; pos++) {
        if (pos == 5) mbar_wait(bars + (B_KV + 1) * 8, 0);
        if (pos == 9) {
#pragma unroll
          for (int d = 1; d < 8; d <<= 1) { sa = __vmaxu2(sa, __shfl_xor_sync(~0u, sa, d)); sc = __vmaxu2(sc, __shfl_xor_sync(~0u, sc, d)); }
          if (lane == 0) { *(uint4*)(sm + SM_STAT + 16) = make_uint4(q_limit(sa), q_limit(sc), sa, sc); mbar_arrive(bars + (B_KV + 4) * 8); }
          mbar_wait(bars + B_FREE0 * 8, 0);
          got = 1;
        }
        if (pos == 13) mbar_wait(bars + B_FREE1 * 8, 0);
        while ((pos == 8 ? rdy != 0xff : !(rdy & ~got)) && ++c < SPIN_LIMIT) {
          uint32_t e0, e1;
          asm volatile("ld.acquire.gpu.global.v4.u32 {%0, %1, %2, %3}, [%4];" : "=r"(sa), "=r"(e0), "=r"(sc), "=r"(e1) : "l"(fp) : "memory");
          rdy = __ballot_sync(~0u, e0 == epoch && e1 == epoch) & 0xff;
          fence_async_g();
        }
        const int i = __ffs(rdy & ~got) - 1;
        got |= 1u << i;
        const uint32_t bar = bars + (B_KV + (pos < 3 ? 0 : pos < 5 ? 1 : pos < 9 ? 2 : pos < 13 ? 4 : 3)) * 8;
        if (elect()) {
          mbar_expect(bar, 2 * SLOT);
          bulk(sb + (pos < 9 ? pos : pos - 9) * 2 * SLOT, g_kv + (hp * 16 + (pos < 9 ? 0 : 8) + ((tq + i) & 7)) * 1024, 2 * SLOT, bar);
        }
        TSTAMP(5, lane == 0 && pos == 2)
      }
    }
    __syncwarp();
    const unsigned long long u0 = cell_ld(g_g + rt3 * 64 + lane), u1 = cell_ld(g_g + rt3 * 64 + 32 + lane);
    if (elect()) {
      mbar_expect(bars + B_X * 8, 16384);
      tma2d(sb + SM_X, &P.xr, cs * 128, rt3 * 64, bars + B_X * 8);
      tma2d(sb + SM_X + 8192, &P.xr, cs * 128 + 64, rt3 * 64, bars + B_X * 8);
      mbar_expect(bars + B_WO * 8, 98304);
#pragma unroll
      for (int j = 0; j < 3; j++) tma2d(sb + SM_WO + j * 32768, &P.wo, cs * 128 + (j ? 64 : 0), (j >> 1) * 256, bars + B_WO * 8);
    }
    __syncwarp();
#pragma unroll
    for (int i = 0; i < 2; i++) {
      const float g = __uint_as_float(cell_fin(g_g + rt3 * 64 + i * 32 + lane, i ? u1 : u0, epoch));
      *(uint2*)(sm + SM_G + i * 256 + lane * 8) = make_uint2(pack_b2(g, g), pack_b2(1.f - g, 1.f - g));
    }
    mbar_wait(bars + B_ORDY * 8, 0);
    if (lane == 0) asm volatile("st.release.gpu.global.u32 [%0], %1;" ::"l"(g_f2 + cta), "r"(epoch) : "memory");
    mbar_wait(bars + B_FREE2 * 8, 0);
    if (elect()) { mbar_expect(bars + B_WO * 8, 32768); tma2d(sb + SM_WO3, &P.wo, cs * 128, 256, bars + B_WO * 8); }
    __syncwarp();
    uint32_t v, c = 0;
    do {
      asm volatile("ld.acquire.gpu.global.u32 %0, [%1];" : "=r"(v) : "l"(g_f2 + tq * 16 + (lane & 15)) : "memory");
      if (++c > SPIN_LIMIT) break;
    } while (!__all_sync(~0u, v == epoch));
    if (elect()) {
      fence_async_g();
      mbar_expect(bars + B_OA * 8, 32768);
      bulk(sb + SM_OA, g_o + rt3 * 4096, 32768, bars + B_OA * 8);
    }
    __syncwarp();
    uint32_t idx, e;
    c = 0;
    do {
      asm volatile("ld.acquire.gpu.global.v2.u32 {%0, %1}, [%2];" : "=r"(idx), "=r"(e) : "l"(g_fy + (lane & 3)) : "memory");
      if (++c > SPIN_LIMIT) break;
    } while (!__all_sync(~0u, e == epoch));
    mbar_wait(bars + B_X * 8, 0);
#pragma unroll 1
    for (int t = 0; t < 2; t++) {
      const uint32_t d = ((idx >> (16 * t)) & 0xffff) - rt3 * 64;
      if (d < 64) {
        float4 y[NFFN];
#pragma unroll
        for (int f = 0; f < NFFN; f++) y[f] = __ldcg((const float4*)(g_y + (f * 2 + t) * DM + cs * 128) + lane);
        uint2* xp = (uint2*)(sm + SM_X + (lane >> 4) * 8192 + d * 128 + ((((lane >> 1) ^ d) & 7) << 4) + (lane & 1) * 8);
        const uint2 xv = *xp;
        *xp = make_uint2(pack_b2(b_lo(xv.x) + ((y[0].x + y[1].x) + (y[2].x + y[3].x)), b_hi(xv.x) + ((y[0].y + y[1].y) + (y[2].y + y[3].y))),
                         pack_b2(b_lo(xv.y) + ((y[0].z + y[1].z) + (y[2].z + y[3].z)), b_hi(xv.y) + ((y[0].w + y[1].w) + (y[2].w + y[3].w))));
      }
    }
    __syncwarp();
    if (lane == 0) { mbar_arrive(bars + B_Y * 8); g_epoch[cta] = epoch; }
    TSTAMP(15, lane == 0)
    return;
  }

  uint32_t q[4], q2[4], qn[2];
  {
    float acc[48];
#pragma unroll 1
    for (int kc = 0; kc < 8; kc++) {
      const int s = kc >= NSTAGE ? kc - NSTAGE : kc;
      const uint32_t st = sb + (kc < 3 ? kc + 2 : kc - 3) * STG;
      mbar_wait(bars + (B_FULL + s) * 8, kc >= NSTAGE);
      TSTAMP(1, tid == 0 && kc == 0)
      TSTAMPD(13, 8 + kc, tid == 0)
      const uint64_t da = make_desc(st + wg * 8192, 16, 1024, 1), db = make_desc(st + STG_A, 4096, 512, 2);
      wg_fence();
#pragma unroll
      for (int ks = 0; ks < 4; ks++) wg_ss_n96(acc, da + ks * 2, db + ks * 64, kc | ks);
      wg_commit();
      wg_wait<1>();
      if (kc >= 1 && kc <= 4 && lane == 0) mbar_arrive(bars + (B_EMPTY + kc - 1) * 8);
    }
    mbar_wait(bars + (B_EMPTY + 3) * 8, 0);
    wg_wait<0>();
    pin<48>(acc);
    asm volatile("setmaxnreg.inc.sync.aligned.u32 112;");
    TSTAMP(2, tid == 0)
    const uint32_t ka = sb + (wg >> 1) * SLOT + (warp & 7) * 512 + (lane & 15) * 32 + (((lane >> 4) ^ (lane >> 2)) & 1) * 16;
#pragma unroll
    for (int hb = 1; hb >= 0; hb--) {
      uint32_t kk[4], vv[4];
#pragma unroll
      for (int i = 0; i < 4; i++) {
        kk[i] = pack_h2(acc[16 + hb * 8 + 2 * i], acc[17 + hb * 8 + 2 * i]);
        vv[i] = pack_h2(acc[32 + hb * 8 + 2 * i], acc[33 + hb * 8 + 2 * i]);
      }
      stsm4(ka + (1 - hb) * 2 * SLOT, kk);
      stsm4(ka + (1 - hb) * 2 * SLOT + 4096, vv);
    }
    fence_async();
#pragma unroll
    for (int hb = 0; hb < 2; hb++) {
      const float* v = acc + 32 + hb * 8;
      uint32_t vm = 0;
#pragma unroll
      for (int i = 0; i < 8; i++) vm = max(vm, __float_as_uint(v[i]) & 0x7fffffffu);
      vm = __reduce_max_sync(~0u, vm);
      const uint32_t kn = max_norm2(acc + 16 + hb * 8);
      if (lane < 2) atomicMax((uint32_t*)(sm + SM_STAT + hb * 8 + lane * 4), lane ? vm : kn);
      qn[hb] = max_norm2(acc + hb * 8);
    }
#pragma unroll
    for (int i = 0; i < 4; i++) { q2[i] = pack_h2(acc[2 * i] * QS, acc[2 * i + 1] * QS); q[i] = pack_h2(acc[8 + 2 * i] * QS, acc[9 + 2 * i] * QS); }
  }
  bar_sync(1, NTHR);
  TSTAMP(3, tid == 0)

  uint32_t* const op = (uint32_t*)g_o + __reduce_max_sync(~0u, (uint32_t)(((tq * 4 + wg) * 4096 + hp * 128 + wi * 32) * 4));
  uint32_t redo = 0;
  const uint32_t park = sb + SM_PARK + tid * 16;
  sts128(park, q2); sts128(park + 8192, q);
  {
    uint32_t cb, cm, ce, c16;
    asm volatile("ld.volatile.shared.v4.u32 {%0, %1, %2, %3}, [%4];" : "=r"(cb), "=r"(cm), "=r"(ce), "=r"(c16) : "r"(sb + SM_STAT + 32));
    uint64_t dk = kv_desc(sb);
    uint32_t bs, ba;
    asm volatile("ld.volatile.shared.v2.u32 {%0, %1}, [%2];" : "=r"(bs), "=r"(ba) : "r"(sb + SM_STAT + 48 + wg * 8));
    uint32_t tab = sb + SM_TAB + wg * 64, src = sb + SM_STAT + 80, ss = 0;
    uint32_t s[32], p[32], o[12];
    wg_fence(); wg_qk(s, q, dk); wg_commit();
    if (wg == 3) bar_arrive(4, 256);
#pragma unroll 1
    for (int ph = 0;; ph++) {
      lds128(o, src); lds64(o + 4, src + 2 * ss); lds128(o + 6, src + ss); lds64(o + 10, src + 2 * ss + 8);
      __syncwarp();
      if (ss && lane == 0) mbar_arrive(bars + B_FREE1 * 8);
      pin<12>(o);
      wg_wait<0>();
      pin<32>(s);
#pragma unroll 1
      for (;;) {
        uint32_t ex[2];
        lds64(ex, tab);
        tab += 8;
#pragma unroll 1
        do {
          desc_step(dk, (int)VT);
          exp2_tile(s, p, cb, cm, ce, c16);
          wg_fence();
          wg_pv(o, p, dk - 8 * VK);
          bar_sync(bs, 256);
#pragma unroll
          for (int j = 1; j < 8; j++) wg_pv(o + (j & 1) * 6, p + j * 4, dk - (8 - j) * VK);
          wg_qk(s, q, dk + QKO);
          wg_commit();
          bar_arrive(ba, 256);
          wg_wait<0>();
          pin<32>(s);
        } while ((uint32_t)dk != ex[0]);
        if (!ex[1]) break;
        mbar_wait(ex[1], wg & 1);
        asm volatile("{.reg .pred p; setp.eq.u32 p, %1, 256; @p mbarrier.arrive.shared::cta.b64 _, [%0];}" ::"r"(ex[1]), "r"(tid & 0x11f) : "memory");
        __syncwarp();
      }
      pin<12>(o);
      const int hb = ph >> 1;
      TSTAMPD(12, tid ? 16 : 10 + hb * 2, tid == 0 || tid == 384)
      if (!hb) {
        lds128(q, park + ph * 8192);
        desc_step(dk, ph * (int)(-NSLOT * VT));
        if (ph) mbar_wait(bars + (B_KV + 4) * 8, 0);
        wg_fence(); wg_qk(s, q, dk); wg_commit();
      }
      if (ph == 0) {
        sts128(park + 16384, o); sts128(park + 24576, o + 6); sts64(park + 32768, o + 4); sts64(park + 32776, o + 10);
        continue;
      }
      uint32_t lim;
      asm volatile("ld.shared.u32 %0, [%1];" : "=r"(lim) : "r"(sb + SM_STAT + 12 + ph * 4));
      uint32_t l2, ok;
#pragma unroll
      for (int i = 0; i < 6; i++) asm("add.f16x2 %0, %0, %1;" : "+r"(o[i]) : "r"(o[6 + i]));
      float i0, i1;
      asm("rcp.approx.ftz.f32 %0, %1;" : "=f"(i0) : "f"(h_lo(o[4])));
      asm("rcp.approx.ftz.f32 %0, %1;" : "=f"(i1) : "f"(h_lo(o[5])));
      l2 = __byte_perm(o[4], o[5], 0x5410);
#pragma unroll
      for (int i = 0; i < 4; i++) asm("fma.rn.f16x2 %0, %1, %2, %0;" : "+r"(l2) : "r"(o[i]), "r"(0));
      asm("{.reg .pred a, b, c, d; setp.ge.f16x2 a|b, %1, %2; setp.le.and.f16x2 c|d, %1, %3, a; and.pred c, c, d; and.pred c, c, b; selp.u32 %0, 1, 0, c;}"
        : "=r"(ok) : "r"(l2), "r"(0x54005400), "r"(0x7bff7bff));
      uint32_t* dst = op + hb * 8192 + lane;
      if (__all_sync(~0u, ok && (hb ? qn[1] : qn[0]) < lim)) {
#pragma unroll
        for (int i = 0; i < 4; i++) o_store(dst + (i & 1) * 64 + (i >> 1) * 32, pack_b2(h_lo(o[i]) * ((i & 1) ? i1 : i0), h_hi(o[i]) * ((i & 1) ? i1 : i0)));
        __syncwarp();
        if (!hb && lane == 0) mbar_arrive(bars + B_ORDY * 8);
      } else {
        redo |= 1 << hb;
        if (!hb) { lds128(o, park); ((uint4*)op)[lane] = make_uint4(o[0], o[1], o[2], o[3]); }
      }
      if (hb) break;
      src = park + 16384; ss = 8192;
    }
    wg_wait<0>();
  }
  TSTAMP(17, tid == 384)
  if (redo) {
#pragma unroll 1
    for (int hb = 0; hb < 2; hb++) {
      const bool in_range = kv_in_range(*(const uint32_t*)(sm + SM_STAT + 24 + hb * 4)) && __uint_as_float(hb ? qn[1] : qn[0]) * (QS * QS) <= 1.6e7f;
      const uint32_t m = (redo >> hb & 1) ? (in_range ? 1 : 3) : 0;
      if (m == 1) {
        const uint4 t = hb ? make_uint4(q[0], q[1], q[2], q[3]) : ((const uint4*)op)[lane];
        attn_true_max(t.x, t.y, t.z, t.w, hp * 2 + hb, op + hb * 8192);
      }
      if (m == 3) attn_fp32(P.px, P.pw, hp * 2 + hb, tq * 256 + warp * 16, op + hb * 8192);
      __syncwarp();
      if (m && !hb && lane == 0) mbar_arrive(bars + B_ORDY * 8);
    }
  }

  const uint64_t db0 = make_desc(sb + SM_WO, 32768, 1024, 1), db1 = make_desc(sb + SM_WO3, SM_WO + 65536 - SM_WO3, 1024, 1);
  if (wg == 1 || wg == 2) {
    const int w = warp - 4;
    const uint4* src = g_o + rt3 * 4096 + 2048 + w * 256 + lane;
    uint4 v[8];
    const uint64_t entry = (make_desc(sb + SM_OB + w * 4096, 128, 0, 0) << 32) | ((uint32_t)(w < 4 ? db0 : db1) + wi * 512 + 128);
    mbar_wait(bars + B_OA * 8, 0);
    TSTAMP(26, lane == 0 && w == 4)
    uint32_t todo = 0xff;
    for (uint32_t c = 0; todo; c++) {
      if (c > SPIN_LIMIT) break;
#pragma unroll
      for (int i = 0; i < 8; i++)
        if (todo >> i & 1) asm volatile("ld.relaxed.gpu.global.v4.u32 {%0, %1, %2, %3}, [%4];" : "=r"(v[i].x), "=r"(v[i].y), "=r"(v[i].z), "=r"(v[i].w) : "l"(src + i * 32) : "memory");
#pragma unroll
      for (int i = 0; i < 8; i++)
        if (__all_sync(~0u, min(min(v[i].x, v[i].y), min(v[i].z, v[i].w)) != 0)) todo &= ~(1u << i);
      TSTAMP(18, lane == 0 && w == 4 && c == 0)
    }
    uint32_t t = 0;
    if (lane == 0) t = atomicAdd((uint32_t*)(sm + SM_ORD + 72), 8);
#pragma unroll
    for (int i = 0; i < 8; i++) *(uint4*)(sm + SM_OB + w * 4096 + i * 512 + lane * 16) = v[i];
    fence_async();
    __syncwarp();
    if (lane == 0) asm volatile("st.release.cta.shared.u64 [%0], %1;" ::"r"(sb + SM_ORD + t), "l"(entry) : "memory");
    TSTAMPD(8, w ? 25 : 8, lane == 0 && wi == 0)
  } else if (wg == 0) {
    float acc[64];
    uint32_t pre[32];
    const uint32_t stg = sb + SM_X + wi * 2048;
    const uint32_t fr = stg + (lane & 15) * 128 + (((lane >> 4) ^ lane) & 7) * 16;
    mbar_wait(bars + B_WO * 8, 0);
    mbar_wait(bars + B_OA * 8, 0);
    mbar_wait(bars + B_Y * 8, 0);
    uint32_t g[4];
    lds64(g, sb + SM_G + (wi * 16 + (lane >> 2)) * 8); lds64(g + 2, sb + SM_G + (wi * 16 + 8 + (lane >> 2)) * 8);
#pragma unroll
    for (int j = 0; j < 8; j++) ldsm4(pre + j * 4, (fr ^ (j & 3) * 32) + (j >> 2) * 8192);
#pragma unroll
    for (int i = 0; i < 32; i++) asm("mul.rn.bf16x2 %0, %0, %1;" : "+r"(pre[i]) : "r"(g[(i & 1) * 2 + 1]));
    pin<32>(pre);
    TSTAMP(20, tid == 0)
    bar_sync(4, 256);
    wg_fence();
#pragma unroll
    for (int ks = 0; ks < 16; ks++) wg_ss_n128(acc, make_desc(sb + SM_OA, 128, 256, 0) + ks * 128, (ks < 8 ? db0 : db1) + (ks & 7) * 256, ks);
    wg_commit();
    TSTAMP(19, tid == 0)
    uint64_t e = 0;
    uint4* dst = (uint4*)(P.pout + (rt3 * 64 + wi * 16 + (lane >> 3)) * DM + cs * 128) + (lane & 7);
    uint32_t rd = stg + (lane >> 3) * 128 + ((lane ^ lane >> 3) & 7) * 16;
    asm volatile("" : "+l"(dst), "+r"(rd));
#pragma unroll
    for (int t = 0; t < 8; t++) {
      asm volatile("{.reg .pred p; .reg .b32 c;\n"
        "setp.ne.u64 p, %0, 0;\n"
        "@p bra.uni DONE;\n"
        "mov.b32 c, 0;\n"
        "LOOP: ld.acquire.cta.shared.u64 %0, [%1];\n"
        "add.u32 c, c, 1;\n"
        "setp.eq.u64 p, %0, 0;\n"
        "setp.lt.and.u32 p, c, %2, p;\n"
        "@p bra.uni LOOP;\n"
        "DONE: }" : "+l"(e) : "r"(sb + SM_ORD + t * 8), "n"(SPIN_LIMIT * 32) : "memory");
      if (t == 7) { TSTAMP(24, tid == 0) }
      const uint64_t da = make_desc(0, 0, 256, 0) | e >> 32, db = make_desc(0, 0, 1024, 1) | (uint32_t)e;
      if (t < 7) asm volatile("ld.acquire.cta.shared.u64 %0, [%1];" : "=l"(e) : "r"(sb + SM_ORD + t * 8 + 8) : "memory");
      wg_fence();
      wg_ss_n128(acc, da, db, 1);
      wg_ss_n128(acc, da + 128, db + 256, 1);
      wg_commit();
    }
    wg_wait<0>();
    pin<64>(acc);
    TSTAMP(9, tid == 0)
#pragma unroll
    for (int h = 0; h < 2; h++) {
#pragma unroll
      for (int j = h * 4; j < h * 4 + 4; j++) {
#pragma unroll
        for (int i = j * 4; i < j * 4 + 4; i++) asm("fma.rn.bf16x2 %0, %1, %2, %0;" : "+r"(pre[i]) : "r"(pack_b2(acc[2 * i], acc[2 * i + 1])), "r"(g[(i & 1) * 2]));
        stsm4((fr ^ (j & 3) * 32) + h * 8192, pre + j * 4);
      }
      __syncwarp();
#pragma unroll
      for (int j = 0; j < 4; j++) {
        uint32_t r[4];
        lds128(r, (rd ^ (j & 1) * 64) + j * 512 + h * 8192);
        dst[j * 4 * DM / 8 + h * 8] = make_uint4(r[0], r[1], r[2], r[3]);
      }
    }
    TSTAMP(7, tid == 0)
  }
}

typedef CUresult (*EncodeFn)(CUtensorMap*, CUtensorMapDataType, cuuint32_t, void*, const cuuint64_t*, const cuuint64_t*,
                             const cuuint32_t*, const cuuint32_t*, CUtensorMapInterleave, CUtensorMapSwizzle,
                             CUtensorMapL2promotion, CUtensorMapFloatOOBfill);
static void make_map(EncodeFn enc, CUtensorMap* m, const void* p, int cols, int rows, int box_rows) {
  cuuint64_t dim[2] = {(cuuint64_t)cols, (cuuint64_t)rows}, str[1] = {(cuuint64_t)cols * 2};
  cuuint32_t box[2] = {64, (cuuint32_t)box_rows}, es[2] = {1, 1};
  enc(m, CU_TENSOR_MAP_DATA_TYPE_BFLOAT16, 2, (void*)p, dim, str, box, es, CU_TENSOR_MAP_INTERLEAVE_NONE,
      CU_TENSOR_MAP_SWIZZLE_128B, CU_TENSOR_MAP_L2_PROMOTION_L2_128B, CU_TENSOR_MAP_FLOAT_OOB_FILL_NONE);
}

extern "C" void kernel_launch(void* const* d_in, const int* in_sizes, int n_in, void* d_out, int out_size) {
  static EncodeFn enc = nullptr;
  if (!enc) {
    void* fn = nullptr; cudaDriverEntryPointQueryResult qr;
    cudaGetDriverEntryPoint("cuTensorMapEncodeTiled", &fn, cudaEnableDefault, &qr);
    enc = (EncodeFn)fn;
    cudaFuncSetAttribute(fused_kernel, cudaFuncAttributeMaxDynamicSharedMemorySize, SM_TOTAL);
  }
  Params P;
  make_map(enc, &P.x, d_in[0], DM, SEQ, 256);
  make_map(enc, &P.wo, d_in[2], DM, DM, 256);
  make_map(enc, &P.xr, d_in[0], DM, SEQ, 64);
  make_map(enc, &P.wg, d_in[5], FF, DM, 256);
  make_map(enc, &P.wu, d_in[6], FF, DM, 256);
  make_map(enc, &P.wd, d_in[7], DM, FF, 224);
  {
    cuuint64_t dim[3] = {DM, DM, 3}, str[2] = {3 * DM * 2, DM * 2};
    cuuint32_t box[3] = {32, 64, 3}, es[3] = {1, 1, 1};
    enc(&P.w, CU_TENSOR_MAP_DATA_TYPE_BFLOAT16, 3, d_in[1], dim, str, box, es, CU_TENSOR_MAP_INTERLEAVE_NONE,
        CU_TENSOR_MAP_SWIZZLE_64B, CU_TENSOR_MAP_L2_PROMOTION_L2_128B, CU_TENSOR_MAP_FLOAT_OOB_FILL_NONE);
  }
  P.px = (const bf16*)d_in[0]; P.pw = (const bf16*)d_in[1]; P.pwo = (const bf16*)d_in[2];
  P.pout = (bf16*)d_out;
  P.pwr = (const bf16*)d_in[4]; P.pgw = (const bf16*)d_in[8];
  fused_kernel<<<NCTA, NTHR, SM_TOTAL, cudaStreamPerThread>>>(P);
}
```

```cpp
#include <cuda_runtime.h>
#include <cuda.h>
#include <cuda_bf16.h>
#include <cuda_fp16.h>
#include <stdint.h>

typedef __nv_bfloat16 bf16;

constexpr int SEQ = 2048, DM = 512, NH = 32, FF = 1792;
constexpr int NMAIN = 128, NFFN = 4, NCTA = NMAIN + NFFN, NTHR = 640;
constexpr float QS = 0.25f * 1.4426950408889634f;
constexpr int FSL = FF / NFFN;
#define NMU 10
#define LAG 3
#define QKO 65536
#define LDAT 0x1010100c
#define SHM 4

constexpr int NSTAGE = 5, STG_A = 32768, STG = STG_A + 12288;
constexpr int SLOT = 8192, NSLOT = 18, SM_PARK = NSLOT * SLOT;
constexpr int SM_ONE = 28 * SLOT, SM_BAR = SM_ONE + 512, SM_STAT = SM_BAR + 256, SM_G = SM_STAT + 128, SM_TAB = SM_G + 512;
constexpr int SM_WO3 = 0, SM_OA = 4 * SLOT, SM_WO = 14 * SLOT, SM_X = 26 * SLOT;
constexpr int SM_TOTAL = SM_TAB + 256 + 1024;
constexpr int FSTG = 32768, FNS = 6, SM_XS = FNS * FSTG, SM_HS = SM_XS + 8192, SM_RED = SM_HS + 8192;
constexpr int B_FULL = 0, B_EMPTY = 6, B_KV = 12, B_FREE0 = 17, B_FREE2 = 18, B_ORDY = 19, B_FREE1 = 20, B_X = 21, B_Y = 22, B_OA = 23, B_WO = 24, B_N = 25;

__device__ uint4 g_kv[NH * 16 * 512];
__device__ uint4 g_o[32 * NH * 128];
__device__ uint4 g_f1[NMAIN];
__device__ uint32_t g_f2[NMAIN];
__device__ uint2 g_r[SEQ], g_g[SEQ];
__device__ float g_y[NFFN * 2 * DM];
__device__ uint2 g_fy[NFFN];
__device__ uint32_t g_epoch[NCTA];
#define TSTAMPD(k, i, cond)
#define TSTAMP(i, cond) TSTAMPD(i, i, cond)

struct Params {
  CUtensorMap x, w, wo, xr, wg, wu, wd;
  const bf16 *px, *pw, *pwo, *pwr, *pgw;
  bf16* pout;
};

constexpr uint32_t SPIN_LIMIT = 1u << 21;
__device__ __forceinline__ void wg_fence() { asm volatile("wgmma.fence.sync.aligned;" ::: "memory"); }
__device__ __forceinline__ void wg_commit() { asm volatile("wgmma.commit_group.sync.aligned;" ::: "memory"); }
template <int N> __device__ __forceinline__ void wg_wait() { asm volatile("wgmma.wait_group.sync.aligned %0;" ::"n"(N) : "memory"); }
template <int N> __device__ __forceinline__ void pin(uint32_t* s) {
#pragma unroll
  for (int i = 0; i < N; i++) asm volatile("" : "+r"(s[i])::"memory");
}
template <int N> __device__ __forceinline__ void pin(float* s) {
#pragma unroll
  for (int i = 0; i < N; i++) asm volatile("" : "+f"(s[i])::"memory");
}
__device__ __forceinline__ bool elect() {
  uint32_t p;
  asm volatile("{.reg .pred p; elect.sync _|p, 0xffffffff; selp.u32 %0, 1, 0, p;}" : "=r"(p));
  return p;
}
__device__ __forceinline__ void mbar_init(uint32_t bar, uint32_t cnt) { asm volatile("mbarrier.init.shared::cta.b64 [%0], %1;" ::"r"(bar), "r"(cnt) : "memory"); }
__device__ __forceinline__ void mbar_expect(uint32_t bar, uint32_t bytes) { asm volatile("mbarrier.arrive.expect_tx.shared::cta.b64 _, [%0], %1;" ::"r"(bar), "r"(bytes) : "memory"); }
__device__ __forceinline__ void mbar_arrive(uint32_t bar) { asm volatile("mbarrier.arrive.shared::cta.b64 _, [%0];" ::"r"(bar) : "memory"); }
__device__ __forceinline__ void mbar_wait(uint32_t bar, uint32_t parity) {
  asm volatile("{.reg .pred p; .reg .b32 c;\n"
    "mbarrier.try_wait.parity.shared::cta.b64 p, [%0], %1;\n"
    "@p bra.uni DONE;\n"
    "mov.b32 c, 0;\n"
    "LOOP: mbarrier.try_wait.parity.shared::cta.b64 p, [%0], %1, 1000;\n"
    "@p bra.uni DONE;\n"
    "add.u32 c, c, 1;\n"
    "setp.lt.u32 p, c, %2;\n"
    "@p bra.uni LOOP;\n"
    "DONE: }" ::"r"(bar), "r"(parity), "n"(SPIN_LIMIT) : "memory");
}
__device__ __forceinline__ void tma2d(uint32_t dst, const CUtensorMap* m, int c0, int c1, uint32_t bar) {
  asm volatile("cp.async.bulk.tensor.2d.shared::cluster.global.mbarrier::complete_tx::bytes [%0], [%1, {%3, %4}], [%2];"
    ::"r"(dst), "l"(m), "r"(bar), "r"(c0), "r"(c1) : "memory");
}
__device__ __forceinline__ void tma3d(uint32_t dst, const CUtensorMap* m, int c0, int c1, int c2, uint32_t bar) {
  asm volatile("cp.async.bulk.tensor.3d.shared::cluster.global.mbarrier::complete_tx::bytes [%0], [%1, {%3, %4, %5}], [%2];"
    ::"r"(dst), "l"(m), "r"(bar), "r"(c0), "r"(c1), "r"(c2) : "memory");
}
__device__ __forceinline__ void bulk(uint32_t dst, const void* src, uint32_t bytes, uint32_t bar) {
  asm volatile("cp.async.bulk.shared::cluster.global.mbarrier::complete_tx::bytes [%0], [%1], %2, [%3];"
    ::"r"(dst), "l"(src), "r"(bytes), "r"(bar) : "memory");
}
__device__ __forceinline__ void bulk_out(void* dst, uint32_t src, uint32_t bytes) {
  asm volatile("cp.async.bulk.global.shared::cta.bulk_group [%0], [%1], %2;" ::"l"(dst), "r"(src), "r"(bytes) : "memory");
}
__device__ __forceinline__ void fence_async() { asm volatile("fence.proxy.async.shared::cta;" ::: "memory"); }
__device__ __forceinline__ void fence_async_g() { asm volatile("fence.proxy.async.global;" ::: "memory"); }
__device__ __forceinline__ void bar_sync(int id, int n) { asm volatile("bar.sync %0, %1;" ::"r"(id), "r"(n) : "memory"); }
__device__ __forceinline__ void bar_arrive(int id, int n) { asm volatile("bar.arrive %0, %1;" ::"r"(id), "r"(n) : "memory"); }
__device__ __forceinline__ void stsm4(uint32_t a, const uint32_t* r) {
  asm volatile("stmatrix.sync.aligned.m8n8.x4.shared.b16 [%0], {%1, %2, %3, %4};" ::"r"(a), "r"(r[0]), "r"(r[1]), "r"(r[2]), "r"(r[3]) : "memory");
}
__device__ __forceinline__ void ldsm4(uint32_t* r, uint32_t a) {
  asm volatile("ldmatrix.sync.aligned.m8n8.x4.shared.b16 {%0, %1, %2, %3}, [%4];" : "=r"(r[0]), "=r"(r[1]), "=r"(r[2]), "=r"(r[3]) : "r"(a) : "memory");
}
__device__ __forceinline__ void sts128(uint32_t a, const uint32_t* r) { asm volatile("st.shared.v4.u32 [%0], {%1, %2, %3, %4};" ::"r"(a), "r"(r[0]), "r"(r[1]), "r"(r[2]), "r"(r[3]) : "memory"); }
__device__ __forceinline__ void sts64(uint32_t a, const uint32_t* r) { asm volatile("st.shared.v2.u32 [%0], {%1, %2};" ::"r"(a), "r"(r[0]), "r"(r[1]) : "memory"); }
__device__ __forceinline__ void lds128(uint32_t* r, uint32_t a) { asm volatile("ld.shared.v4.u32 {%0, %1, %2, %3}, [%4];" : "=r"(r[0]), "=r"(r[1]), "=r"(r[2]), "=r"(r[3]) : "r"(a) : "memory"); }
__device__ __forceinline__ void lds64(uint32_t* r, uint32_t a) { asm volatile("ld.shared.v2.u32 {%0, %1}, [%2];" : "=r"(r[0]), "=r"(r[1]) : "r"(a) : "memory"); }
__device__ __forceinline__ void cell_set(uint2* p, uint32_t v, uint32_t e) { asm volatile("st.relaxed.gpu.global.v2.u32 [%0], {%1, %2};" ::"l"(p), "r"(v), "r"(e) : "memory"); }
__device__ __forceinline__ unsigned long long cell_ld(const uint2* p) {
  unsigned long long v;
  asm volatile("ld.relaxed.gpu.global.u64 %0, [%1];" : "=l"(v) : "l"(p) : "memory");
  return v;
}
__device__ __forceinline__ uint32_t cell_fin(const uint2* p, unsigned long long v, uint32_t e) {
  for (uint32_t c = 0; !__all_sync(~0u, (uint32_t)(v >> 32) == e); c++) {
    if (c > SPIN_LIMIT) break;
    v = cell_ld(p);
  }
  return (uint32_t)v;
}
__device__ __forceinline__ uint64_t make_desc(uint32_t addr, uint32_t lbo, uint32_t sbo, uint32_t swz) {
  return (uint64_t)((addr & 0x3FFFF) >> 4) | ((uint64_t)(lbo >> 4) << 16) | ((uint64_t)(sbo >> 4) << 32) | ((uint64_t)swz << 62);
}
constexpr long long VK = 32 - (32 << 16), VT = 512 - (512 << 16);
__device__ __forceinline__ uint64_t kv_desc(uint32_t sb) { return make_desc(sb, SM_ONE, 256, 3); }
__device__ __forceinline__ void desc_step(uint64_t& d, int c) { asm("{.reg .b32 l, h; mov.b64 {l, h}, %0; add.u32 l, l, %1; mov.b64 %0, {l, h};}" : "+l"(d) : "r"(c)); }
__device__ __forceinline__ uint32_t pack_h2(float lo, float hi) { uint32_t r; asm("cvt.rn.f16x2.f32 %0, %1, %2;" : "=r"(r) : "f"(hi), "f"(lo)); return r; }
__device__ __forceinline__ uint32_t pack_b2(float lo, float hi) { uint32_t r; asm("cvt.rn.bf16x2.f32 %0, %1, %2;" : "=r"(r) : "f"(hi), "f"(lo)); return r; }
__device__ __forceinline__ float b_lo(uint32_t v) { return __uint_as_float(v << 16); }
__device__ __forceinline__ float b_hi(uint32_t v) { return __uint_as_float(v & 0xffff0000u); }
__device__ __forceinline__ float h_lo(uint32_t v) { return __half2float(__ushort_as_half((unsigned short)(v & 0xffff))); }
__device__ __forceinline__ float h_hi(uint32_t v) { return __half2float(__ushort_as_half((unsigned short)(v >> 16))); }
__device__ __forceinline__ float sigmoidf(float v) { return 1.f / (1.f + __expf(-v)); }
__device__ __forceinline__ void o_store(uint32_t* p, int odd, int l, int i, uint32_t v) {
  asm volatile("st.relaxed.gpu.global.u32 [%0], %1;" ::"l"(p + (odd ? l * 4 + i : (i & 1) * 64 + (i >> 1) * 32 + l)), "r"(max(v, 1u)) : "memory");
}
__device__ __forceinline__ uint32_t min4(const uint32_t* v, uint32_t k = ~0u) { return min(min(min(min(k, v[0]), v[1]), v[2]), v[3]); }
__device__ __forceinline__ bool missing(const uint32_t* v, uint32_t k = ~0u) { return __any_sync(~0u, min(min(min4(v, k), min4(v + 4, k)), min(min4(v + 8, k), min4(v + 12, k))) == 0); }
__device__ __forceinline__ void o_reload(uint32_t* v, const uint4* p) {
  asm volatile("{.reg .pred p; setp.eq.u32 p, %5, 0; @p ld.relaxed.gpu.global.v4.u32 {%0, %1, %2, %3}, [%4];}"
    : "+r"(v[0]), "+r"(v[1]), "+r"(v[2]), "+r"(v[3]) : "l"(p), "r"(min4(v)) : "memory");
}
__device__ __forceinline__ void o_load(uint32_t* v, const uint4* p) {
  asm volatile("ld.relaxed.gpu.global.v4.u32 {%0, %1, %2, %3}, [%4];" : "=r"(v[0]), "=r"(v[1]), "=r"(v[2]), "=r"(v[3]) : "l"(p) : "memory");
}

__device__ __forceinline__ void wg_rs_n128(float* d, const uint32_t* a, uint64_t db) {
  asm volatile("{.reg .pred p; setp.eq.b32 p, 0, 0;\n"
    "wgmma.mma_async.sync.aligned.m64n128k16.f32.bf16.bf16 {%0,%1,%2,%3,%4,%5,%6,%7,%8,%9,%10,%11,%12,%13,%14,%15,%16,%17,%18,%19,%20,%21,%22,%23,%24,%25,%26,%27,%28,%29,%30,%31,%32,%33,%34,%35,%36,%37,%38,%39,%40,%41,%42,%43,%44,%45,%46,%47,%48,%49,%50,%51,%52,%53,%54,%55,%56,%57,%58,%59,%60,%61,%62,%63}, {%64,%65,%66,%67}, %68, p, 1, 1, 1;}\n"
    : "+f"(d[0]), "+f"(d[1]), "+f"(d[2]), "+f"(d[3]), "+f"(d[4]), "+f"(d[5]), "+f"(d[6]), "+f"(d[7]),
      "+f"(d[8]), "+f"(d[9]), "+f"(d[10]), "+f"(d[11]), "+f"(d[12]), "+f"(d[13]), "+f"(d[14]), "+f"(d[15]),
      "+f"(d[16]), "+f"(d[17]), "+f"(d[18]), "+f"(d[19]), "+f"(d[20]), "+f"(d[21]), "+f"(d[22]), "+f"(d[23]),
      "+f"(d[24]), "+f"(d[25]), "+f"(d[26]), "+f"(d[27]), "+f"(d[28]), "+f"(d[29]), "+f"(d[30]), "+f"(d[31]),
      "+f"(d[32]), "+f"(d[33]), "+f"(d[34]), "+f"(d[35]), "+f"(d[36]), "+f"(d[37]), "+f"(d[38]), "+f"(d[39]),
      "+f"(d[40]), "+f"(d[41]), "+f"(d[42]), "+f"(d[43]), "+f"(d[44]), "+f"(d[45]), "+f"(d[46]), "+f"(d[47]),
      "+f"(d[48]), "+f"(d[49]), "+f"(d[50]), "+f"(d[51]), "+f"(d[52]), "+f"(d[53]), "+f"(d[54]), "+f"(d[55]),
      "+f"(d[56]), "+f"(d[57]), "+f"(d[58]), "+f"(d[59]), "+f"(d[60]), "+f"(d[61]), "+f"(d[62]), "+f"(d[63])
    : "r"(a[0]), "r"(a[1]), "r"(a[2]), "r"(a[3]), "l"(db));
}
__device__ __forceinline__ void wg_qk(uint32_t* d, const uint32_t* a, uint64_t desc) {
  asm volatile("{.reg .pred p; setp.ne.b32 p, 0, 0;\n"
    "wgmma.mma_async.sync.aligned.m64n128k16.f16.f16.f16 {%0,%1,%2,%3,%4,%5,%6,%7,%8,%9,%10,%11,%12,%13,%14,%15,%16,%17,%18,%19,%20,%21,%22,%23,%24,%25,%26,%27,%28,%29,%30,%31}, {%32,%33,%34,%35}, %36, p, 1, 1, 0;}\n"
    : "=r"(d[0]), "=r"(d[1]), "=r"(d[2]), "=r"(d[3]), "=r"(d[4]), "=r"(d[5]), "=r"(d[6]), "=r"(d[7]),
      "=r"(d[8]), "=r"(d[9]), "=r"(d[10]), "=r"(d[11]), "=r"(d[12]), "=r"(d[13]), "=r"(d[14]), "=r"(d[15]),
      "=r"(d[16]), "=r"(d[17]), "=r"(d[18]), "=r"(d[19]), "=r"(d[20]), "=r"(d[21]), "=r"(d[22]), "=r"(d[23]),
      "=r"(d[24]), "=r"(d[25]), "=r"(d[26]), "=r"(d[27]), "=r"(d[28]), "=r"(d[29]), "=r"(d[30]), "=r"(d[31])
    : "r"(a[0]), "r"(a[1]), "r"(a[2]), "r"(a[3]), "l"(desc));
}
__device__ __forceinline__ void wg_pv(uint32_t* d, const uint32_t* a, uint64_t desc) {
  asm volatile("{.reg .pred p; setp.eq.b32 p, 0, 0;\n"
    "wgmma.mma_async.sync.aligned.m64n24k16.f16.f16.f16 {%0,%1,%2,%3,%4,%5}, {%6,%7,%8,%9}, %10, p, 1, 1, 1;}\n"
    : "+r"(d[0]), "+r"(d[1]), "+r"(d[2]), "+r"(d[3]), "+r"(d[4]), "+r"(d[5])
    : "r"(a[0]), "r"(a[1]), "r"(a[2]), "r"(a[3]), "l"(desc));
}
__device__ __forceinline__ void wg_ss_n96(float* d, uint64_t da, uint64_t db, int acc) {
  asm volatile("{.reg .pred p; setp.ne.b32 p, %50, 0;\n"
    "wgmma.mma_async.sync.aligned.m64n96k16.f32.bf16.bf16 {%0,%1,%2,%3,%4,%5,%6,%7,%8,%9,%10,%11,%12,%13,%14,%15,%16,%17,%18,%19,%20,%21,%22,%23,%24,%25,%26,%27,%28,%29,%30,%31,%32,%33,%34,%35,%36,%37,%38,%39,%40,%41,%42,%43,%44,%45,%46,%47}, %48, %49, p, 1, 1, 0, 1;}\n"
    : "+f"(d[0]), "+f"(d[1]), "+f"(d[2]), "+f"(d[3]), "+f"(d[4]), "+f"(d[5]), "+f"(d[6]), "+f"(d[7]),
      "+f"(d[8]), "+f"(d[9]), "+f"(d[10]), "+f"(d[11]), "+f"(d[12]), "+f"(d[13]), "+f"(d[14]), "+f"(d[15]),
      "+f"(d[16]), "+f"(d[17]), "+f"(d[18]), "+f"(d[19]), "+f"(d[20]), "+f"(d[21]), "+f"(d[22]), "+f"(d[23]),
      "+f"(d[24]), "+f"(d[25]), "+f"(d[26]), "+f"(d[27]), "+f"(d[28]), "+f"(d[29]), "+f"(d[30]), "+f"(d[31]),
      "+f"(d[32]), "+f"(d[33]), "+f"(d[34]), "+f"(d[35]), "+f"(d[36]), "+f"(d[37]), "+f"(d[38]), "+f"(d[39]),
      "+f"(d[40]), "+f"(d[41]), "+f"(d[42]), "+f"(d[43]), "+f"(d[44]), "+f"(d[45]), "+f"(d[46]), "+f"(d[47])
    : "l"(da), "l"(db), "r"(acc));
}
__device__ __forceinline__ void wg_ss_n128(float* d, uint64_t da, uint64_t db, int acc) {
  asm volatile("{.reg .pred p; setp.ne.b32 p, %66, 0;\n"
    "wgmma.mma_async.sync.aligned.m64n128k16.f32.bf16.bf16 {%0,%1,%2,%3,%4,%5,%6,%7,%8,%9,%10,%11,%12,%13,%14,%15,%16,%17,%18,%19,%20,%21,%22,%23,%24,%25,%26,%27,%28,%29,%30,%31,%32,%33,%34,%35,%36,%37,%38,%39,%40,%41,%42,%43,%44,%45,%46,%47,%48,%49,%50,%51,%52,%53,%54,%55,%56,%57,%58,%59,%60,%61,%62,%63}, %64, %65, p, 1, 1, 0, 1;}\n"
    : "+f"(d[0]), "+f"(d[1]), "+f"(d[2]), "+f"(d[3]), "+f"(d[4]), "+f"(d[5]), "+f"(d[6]), "+f"(d[7]),
      "+f"(d[8]), "+f"(d[9]), "+f"(d[10]), "+f"(d[11]), "+f"(d[12]), "+f"(d[13]), "+f"(d[14]), "+f"(d[15]),
      "+f"(d[16]), "+f"(d[17]), "+f"(d[18]), "+f"(d[19]), "+f"(d[20]), "+f"(d[21]), "+f"(d[22]), "+f"(d[23]),
      "+f"(d[24]), "+f"(d[25]), "+f"(d[26]), "+f"(d[27]), "+f"(d[28]), "+f"(d[29]), "+f"(d[30]), "+f"(d[31]),
      "+f"(d[32]), "+f"(d[33]), "+f"(d[34]), "+f"(d[35]), "+f"(d[36]), "+f"(d[37]), "+f"(d[38]), "+f"(d[39]),
      "+f"(d[40]), "+f"(d[41]), "+f"(d[42]), "+f"(d[43]), "+f"(d[44]), "+f"(d[45]), "+f"(d[46]), "+f"(d[47]),
      "+f"(d[48]), "+f"(d[49]), "+f"(d[50]), "+f"(d[51]), "+f"(d[52]), "+f"(d[53]), "+f"(d[54]), "+f"(d[55]),
      "+f"(d[56]), "+f"(d[57]), "+f"(d[58]), "+f"(d[59]), "+f"(d[60]), "+f"(d[61]), "+f"(d[62]), "+f"(d[63])
    : "l"(da), "l"(db), "r"(acc));
}
__device__ __forceinline__ void wg_ss_n8(float* d, uint64_t da, uint64_t db, int acc) {
  asm volatile("{.reg .pred p; setp.ne.b32 p, %6, 0;\n"
    "wgmma.mma_async.sync.aligned.m64n8k16.f32.bf16.bf16 {%0,%1,%2,%3}, %4, %5, p, 1, 1, 1, 0;}\n"
    : "+f"(d[0]), "+f"(d[1]), "+f"(d[2]), "+f"(d[3])
    : "l"(da), "l"(db), "r"(acc));
}

__device__ __forceinline__ void exp2_tile(const uint32_t* s, uint32_t* p, uint32_t cb, uint32_t cm, uint32_t ce, uint32_t c16) {
  constexpr int NS = 32 - NMU, L = LAG, STEPS = NS + 3 * L + 2;
  const uint32_t* sw = s + NMU;
  uint32_t y[NS], m[NS], e[NS];
  uint16_t lo[NMU], hi[NMU];
  int issued = 0, packed = 0;
#pragma unroll
  for (int st = 0; st < STEPS; st++) {
    int tgt = ((st + 1) * NMU * 2 + NS - 1) / NS;
    if (tgt > NMU * 2) tgt = NMU * 2;
#pragma unroll
    for (int k = 0; k < 4; k++)
      if (issued < tgt) {
        int r = issued >> 1;
        if (issued & 1) asm volatile("{.reg .b16 a,b; mov.b32 {a,b}, %1; ex2.approx.f16 %0, b;}" : "=h"(hi[r]) : "r"(s[r]));
        else asm volatile("{.reg .b16 a,b; mov.b32 {a,b}, %1; ex2.approx.f16 %0, a;}" : "=h"(lo[r]) : "r"(s[r]));
        issued++;
      }
    if (st < NS) asm volatile("fma.rn.relu.f16x2 %0, %1, %2, %3;" : "=r"(y[st]) : "r"(sw[st]), "r"(0x00400040), "r"(cb));
    if (st >= L && st - L < NS) {
      if ((st - L) % SHM == SHM - 1) asm volatile("mul.lo.u32 %0, %0, 16;" : "+r"(y[st - L]));
      else asm volatile("mul.lo.u32 %0, %0, %1;" : "+r"(y[st - L]) : "r"(c16));
    }
    if (st >= 2 * L && st - 2 * L < NS) {
      int i = st - 2 * L;
      asm volatile("lop3.b32 %0, %1, 0x03ff03ff, %2, 0xEA;" : "=r"(m[i]) : "r"(y[i]), "r"(cm));
      asm volatile("lop3.b32 %0, %1, 0x7c007c00, %2, 0xEA;" : "=r"(e[i]) : "r"(y[i]), "r"(ce));
    }
    if (st >= 3 * L && st - 3 * L < NS) {
      int i = st - 3 * L;
      asm volatile("fma.rn.f16x2 %0, %1, %2, %3;" : "=r"(p[NMU + i]) : "r"(y[i]), "r"(m[i]), "r"(e[i]));
    }
    int tp = st >= 5 ? ((st - 4) * NMU * 2 + NS - 1) / NS / 2 : 0;
    if (tp > NMU || st == STEPS - 1) tp = NMU;
#pragma unroll
    for (int k = 0; k < 8; k++)
      if (packed < tp) {
        asm volatile("mov.b32 %0, {%1, %2};" : "=r"(p[packed]) : "h"(lo[packed]), "h"(hi[packed]));
        packed++;
      }
  }
}

__device__ __forceinline__ void mma16816(float* d, const uint32_t* a, uint32_t b0, uint32_t b1) {
  asm volatile("mma.sync.aligned.m16n8k16.row.col.f32.f16.f16.f32 {%0,%1,%2,%3}, {%4,%5,%6,%7}, {%8,%9}, {%0,%1,%2,%3};"
    : "+f"(d[0]), "+f"(d[1]), "+f"(d[2]), "+f"(d[3]) : "r"(a[0]), "r"(a[1]), "r"(a[2]), "r"(a[3]), "r"(b0), "r"(b1));
}
__device__ __forceinline__ uint32_t mtrans(uint32_t v) { uint32_t r; asm volatile("movmatrix.sync.aligned.m8n8.trans.b16 %0, %1;" : "=r"(r) : "r"(v)); return r; }

__device__ __noinline__ void attn_true_max(uint32_t q0, uint32_t q1, uint32_t q2, uint32_t q3, int head, uint32_t* op) {
  const int lane = threadIdx.x & 31;
  const uint32_t q[4] = {q0, q1, q2, q3};
  const uint32_t* kp = (const uint32_t*)(g_kv + head * 8192) + (lane >> 2) * 8 + (lane & 3);
  const int x0 = (lane >> 4) * 4;
  float m0 = -INFINITY, m1 = -INFINITY, l0 = 0.f, l1 = 0.f, o[2][4] = {};
#pragma unroll 1
  for (int kb = 0; kb < 64; kb++) {
    const int off = (kb >> 2) * 2048 + (kb & 3) * 256;
    uint32_t kf[8], vf[8];
#pragma unroll
    for (int i = 0; i < 8; i++) { const uint32_t* a = kp + off + (i >> 1) * 64 + (((i & 1) * 4) ^ x0); kf[i] = __ldcg(a); vf[i] = __ldcg(a + 1024); }
    float s[4][4] = {};
#pragma unroll
    for (int i = 0; i < 4; i++) mma16816(s[i], q, kf[2 * i], kf[2 * i + 1]);
    float a = m0, b = m1;
#pragma unroll
    for (int i = 0; i < 4; i++) { a = fmaxf(a, fmaxf(s[i][0], s[i][1])); b = fmaxf(b, fmaxf(s[i][2], s[i][3])); }
#pragma unroll
    for (int d = 1; d < 4; d <<= 1) { a = fmaxf(a, __shfl_xor_sync(~0u, a, d)); b = fmaxf(b, __shfl_xor_sync(~0u, b, d)); }
    const float c0 = exp2f(m0 - a), c1 = exp2f(m1 - b);
    m0 = a; m1 = b; l0 *= c0; l1 *= c1;
    uint32_t p[8];
#pragma unroll
    for (int i = 0; i < 4; i++) {
      const float e0 = exp2f(s[i][0] - a + 12.f), e1 = exp2f(s[i][1] - a + 12.f), e2 = exp2f(s[i][2] - b + 12.f), e3 = exp2f(s[i][3] - b + 12.f);
      l0 += e0 + e1; l1 += e2 + e3;
      p[2 * i] = pack_h2(e0, e1); p[2 * i + 1] = pack_h2(e2, e3);
    }
#pragma unroll
    for (int c = 0; c < 2; c++) {
      o[c][0] *= c0; o[c][1] *= c0; o[c][2] *= c1; o[c][3] *= c1;
      mma16816(o[c], p, mtrans(vf[c]), mtrans(vf[2 + c]));
      mma16816(o[c], p + 4, mtrans(vf[4 + c]), mtrans(vf[6 + c]));
    }
  }
#pragma unroll
  for (int d = 1; d < 4; d <<= 1) { l0 += __shfl_xor_sync(~0u, l0, d); l1 += __shfl_xor_sync(~0u, l1, d); }
  l0 = 1.f / l0; l1 = 1.f / l1;
  o_store(op, head & 1, lane, 0, pack_b2(o[0][0] * l0, o[0][1] * l0)); o_store(op, head & 1, lane, 1, pack_b2(o[0][2] * l1, o[0][3] * l1));
  o_store(op, head & 1, lane, 2, pack_b2(o[1][0] * l0, o[1][1] * l0)); o_store(op, head & 1, lane, 3, pack_b2(o[1][2] * l1, o[1][3] * l1));
}

__device__ __noinline__ void attn_fp32(const bf16* x, const bf16* w, int head, int row0, uint32_t* op) {
  const int lane = threadIdx.x & 31, r = lane & 15;
  float q[16], o[16], m = -INFINITY, l = 0.f;
#pragma unroll
  for (int d = 0; d < 16; d++) { q[d] = 0.f; o[d] = 0.f; }
#pragma unroll 1
  for (int k = 0; k < DM; k++) {
    const float xv = __bfloat162float(x[(row0 + r) * DM + k]);
#pragma unroll
    for (int d = 0; d < 16; d++) q[d] += xv * __bfloat162float(w[k * 3 * DM + head * 16 + d]);
  }
  const bf16* wc = w + (lane >> 4) * DM + DM + head * 16 + r;
#pragma unroll 1
  for (int key = 0; key < SEQ; key += 8) {
    float a[8] = {};
#pragma unroll 2
    for (int k = 0; k < DM; k++) {
      const float wv = __bfloat162float(wc[k * 3 * DM]);
#pragma unroll
      for (int j = 0; j < 8; j++) a[j] += wv * __bfloat162float(x[(key + j) * DM + k]);
    }
#pragma unroll
    for (int j = 0; j < 8; j++) {
      float sc = 0.f;
#pragma unroll
      for (int d = 0; d < 16; d++) sc += q[d] * __shfl_sync(~0u, a[j], d);
      sc *= 0.25f;
      const float mn = fmaxf(m, sc), c = __expf(m - mn), p = __expf(sc - mn);
      l = l * c + p; m = mn;
#pragma unroll
      for (int d = 0; d < 16; d++) o[d] = o[d] * c + p * __shfl_sync(~0u, a[j], 16 + d);
    }
  }
  l = 1.f / l;
  if (lane < 16) {
#pragma unroll
    for (int i = 0; i < 8; i++) o_store(op, head & 1, (r & 7) * 4 + (i & 3), (r >> 3) + (i >> 2) * 2, pack_b2(o[2 * i] * l, o[2 * i + 1] * l));
  }
}

__device__ __forceinline__ void ffn_cta(const Params& P, uint8_t* sm, uint32_t sb, int f, uint32_t epoch) {
  const int tid = threadIdx.x, lane = tid & 31, warp = __shfl_sync(~0u, tid >> 5, 0);
  const uint32_t bars = sb + SM_BAR;
  if (warp >= 16) {
    if (warp == 16) {
      bar_sync(1, 544);
      if (lane == 0) {
#pragma unroll 1
        for (int i = 0, s = 0, ph = 1; i < 44; i++) {
          const uint32_t bar = bars + (B_FULL + s) * 8;
          if (i >= FNS) mbar_wait(bars + (B_EMPTY + s) * 8, ph);
          if (i < 28) { mbar_expect(bar, 32768); tma2d(sb + s * FSTG, (i & 2) ? &P.wu : &P.wg, f * FSL + (i >> 2) * 64, (i & 1) * 256, bar); }
          else { mbar_expect(bar, 28672); tma2d(sb + s * FSTG, &P.wd, ((i - 28) >> 1) * 64, f * FSL + (i & 1) * 224, bar); }
          if (++s == FNS) { s = 0; ph ^= 1; }
        }
      }
    }
    return;
  }
  unsigned long long* red = (unsigned long long*)(sm + SM_RED);
  unsigned long long key[4], best[2];
#pragma unroll
  for (int i = 0; i < 4; i++) key[i] = cell_ld(g_r + i * 512 + tid);
  *(uint4*)(sm + SM_XS + tid * 16) = make_uint4(0, 0, 0, 0);
  *(uint4*)(sm + SM_HS + tid * 16) = make_uint4(0, 0, 0, 0);
#pragma unroll
  for (int i = 0; i < 4; i++) {
    uint32_t u = cell_fin(g_r + i * 512 + tid, key[i], epoch);
    u = (u & 0x80000000u) ? ~u : (u | 0x80000000u);
    key[i] = ((unsigned long long)u << 32) | (uint32_t)(SEQ - 1 - (i * 512 + tid));
  }
#pragma unroll
  for (int r = 0; r < 2; r++) {
    unsigned long long b = 0;
#pragma unroll
    for (int i = 0; i < 4; i++) if (!(r == 1 && key[i] == best[0]) && key[i] > b) b = key[i];
#pragma unroll
    for (int d = 16; d; d >>= 1) { unsigned long long o = __shfl_xor_sync(~0u, b, d); b = o > b ? o : b; }
    if (lane == 0) red[r * 16 + warp] = b;
    bar_sync(1 + r, r ? 512 : 544);
#pragma unroll
    for (int i = 0; i < 16; i++) b = red[r * 16 + i] > b ? red[r * 16 + i] : b;
    best[r] = b;
  }
  if (warp >= 4) return;
  const int i0 = SEQ - 1 - (int)(uint32_t)best[0], i1 = SEQ - 1 - (int)(uint32_t)best[1];
  *(uint4*)(sm + SM_XS + (tid & 63) * 128 + (tid >> 6) * 16) = __ldg((const uint4*)(P.px + (tid < 64 ? i0 : i1) * DM) + (tid & 63));
  float rs[2];
#pragma unroll
  for (int t = 0; t < 2; t++) {
    const uint32_t u = (uint32_t)(best[t] >> 32);
    rs[t] = sigmoidf(__uint_as_float((u & 0x80000000u) ? (u & 0x7fffffffu) : ~u));
  }
  fence_async();
  bar_sync(3, 128);
  const int row = warp * 16 + (lane >> 2);
  float acc[4], gate[4];
#pragma unroll 1
  for (int i = 0, s = 0, ph = 0; i < 44; i++) {
    mbar_wait(bars + (B_FULL + s) * 8, ph);
    const uint64_t da = make_desc(sb + s * FSTG, 8192, 1024, 1);
    const uint64_t db = make_desc(i < 28 ? sb + SM_XS + (i & 1) * 4096 : sb + SM_HS + (i & 1) * 3584, 128, 256, 0);
    wg_fence();
#pragma unroll
    for (int ks = 0; ks < 14; ks++) wg_ss_n8(acc, da + ks * 128, db + ks * 16, (i & 1) | ks);
    wg_commit();
    if (i < 28) { wg_fence(); wg_ss_n8(acc, da + 14 * 128, db + 14 * 16, 1); wg_ss_n8(acc, da + 15 * 128, db + 15 * 16, 1); wg_commit(); }
    wg_wait<0>();
    pin<4>(acc);
    if (lane == 0) mbar_arrive(bars + (B_EMPTY + s) * 8);
    if (++s == FNS) { s = 0; ph ^= 1; }
    if (i >= 28) {
      if ((i & 1) && (lane & 3) == 0) {
#pragma unroll
        for (int j = 0; j < 4; j++) g_y[(f * 2 + (j & 1)) * DM + ((i - 28) >> 1) * 64 + row + (j >> 1) * 8] = acc[j] * rs[j & 1];
      }
    } else if ((i & 3) == 1) {
#pragma unroll
      for (int j = 0; j < 4; j++) gate[j] = acc[j] * sigmoidf(acc[j]);
    } else if ((i & 3) == 3) {
      if ((lane & 3) == 0) {
#pragma unroll
        for (int j = 0; j < 4; j++)
          *(bf16*)(sm + SM_HS + ((i >> 2) * 8 + warp * 2 + (j >> 1)) * 128 + (j & 1) * 16 + (lane >> 2) * 2) = __float2bfloat16(gate[j] * acc[j]);
      }
      if (i == 27) { fence_async(); bar_sync(3, 128); }
    }
  }
  bar_sync(3, 128);
  if (tid == 0) {
    __threadfence();
    cell_set(g_fy + f, (uint32_t)i0 | ((uint32_t)i1 << 16), epoch);
    g_epoch[NMAIN + f] = epoch;
  }
  TSTAMP(7, tid == 0)
}

__device__ __forceinline__ uint32_t max_norm2(const float* k) {
  float n0 = k[0] * k[0] + k[1] * k[1] + k[4] * k[4] + k[5] * k[5], n1 = k[2] * k[2] + k[3] * k[3] + k[6] * k[6] + k[7] * k[7];
  const bool odd = threadIdx.x & 1;
  n0 = (odd ? n1 : n0) + __shfl_xor_sync(~0u, odd ? n0 : n1, 1);
  n0 += __shfl_xor_sync(~0u, n0, 2);
  return __reduce_max_sync(~0u, __float_as_uint(n0) & 0x7fffffffu);
}

__device__ __forceinline__ bool kv_in_range(uint32_t st) { return b_lo(st) <= 1.6e7f && b_hi(st) >= 6.2e-5f && b_hi(st) <= 6.0e4f; }
__device__ __forceinline__ uint32_t q_limit(uint32_t st) {
  return kv_in_range(st) ? __float_as_uint(fminf(__fdividef(289.f, b_lo(st)), 1.6e7f) * (1.f / (QS * QS))) + 1 : 0;
}

__global__ void __launch_bounds__(NTHR, 1) fused_kernel(const __grid_constant__ Params P) {
  extern __shared__ uint8_t smem_raw[];
  const uint32_t sraw = (uint32_t)__cvta_generic_to_shared(smem_raw);
  const uint32_t sb = (sraw + 1023) & ~1023u;
  uint8_t* sm = smem_raw + (sb - sraw);
  const uint32_t bars = sb + SM_BAR;
  const int tid = threadIdx.x, lane = tid & 31, warp = __shfl_sync(~0u, tid >> 5, 0), wg = warp >> 2, wi = warp & 3;
  const int cta = blockIdx.x, tq = cta >> 4, hp = cta & 15;
  TSTAMP(0, tid == 0)
  uint32_t last = 0;
  if (wg == 4 || cta >= NMAIN) asm volatile("ld.relaxed.gpu.global.u32 %0, [%1];" : "=r"(last) : "l"(g_epoch + cta) : "memory");
  if (warp == 0) {
    if (elect()) {
      asm volatile("prefetch.tensormap [%0];" ::"l"(&P.x) : "memory");
#pragma unroll
      for (int c = 0; c < B_EMPTY; c++) mbar_init(bars + (B_FULL + c) * 8, 1);
      fence_async();
      if (cta < NMAIN) {
#pragma unroll
        for (int c = 0; c < NSTAGE; c++) {
          const uint32_t st = sb + (c < 3 ? c + 2 : c - 3) * STG, bar = bars + (B_FULL + c) * 8;
          mbar_expect(bar, STG);
          tma3d(st + STG_A, &P.w, hp * 32, c * 64, 0, bar);
          tma2d(st, &P.x, c * 64, tq * 256, bar);
          if (c == 0) { TSTAMP(27, true) }
        }
        TSTAMP(28, true)
      }
    }
  } else if (warp == 1) {
    if (elect()) {
#pragma unroll
      for (int c = B_EMPTY; c < B_N; c++)
        mbar_init(bars + c * 8, c < B_KV ? (cta < NMAIN ? 16 : 4) : c < B_ORDY ? (0x4453421 >> (4 * (c - B_KV))) & 15 : c < B_X ? 16 : c < B_WO ? 1 : 2);
      fence_async();
    }
  } else if (warp == 17) {
    *(uint4*)(sm + SM_ONE + lane * 16) = make_uint4(0x3c003c00u, 0x3c003c00u, 0x3c003c00u, 0x3c003c00u);
    if (lane == 0 || lane == 5) *(uint4*)(sm + SM_STAT + lane * 16) = make_uint4(0, 0, 0, 0);
    if (lane == 1) *(uint4*)(sm + SM_STAT + 32) = make_uint4(0x039a039au, 0x38003800u, 0x000b000bu, 16);
    if (lane < 4) *(uint2*)(sm + SM_STAT + 48 + lane * 8) = make_uint2(4 + lane, 4 + ((lane + 1) & 3));
    const uint32_t e = (lane < 8 ? 0x0e071209050302ull : lane < 24 ? 0x0e1202ull : 0x0e09120902ull) >> (lane & 7) * 8 & 255;
    const uint32_t b = (lane < 8 ? 0x0f000e0d0c00ull : lane < 24 ? 0ull : 0x12001100ull) >> (lane & 7) * 8 & 255;
    *(uint2*)(sm + SM_TAB + lane * 8) = make_uint2((uint32_t)kv_desc(sb) + e * (uint32_t)VT, b ? bars + b * 8 : 0);
    fence_async();
  }
  __syncthreads();
  TSTAMP(29, tid == 0)
  if (cta >= NMAIN) { ffn_cta(P, sm, sb, cta - NMAIN, last + 1); return; }
  const int rt3 = tq * 4 + (hp >> 2), cs = hp & 3;

  if (wg == 4) {
    const uint32_t epoch = last + 1;
    if (wi != 0) {
      const uint4* wr = (const uint4*)P.pwr; const uint4* gw = (const uint4*)P.pgw;
      const int t0 = cta * 16 + (wi - 1) * 5;
      uint4 xv[6][2], a[2], b[2];
#pragma unroll
      for (int t = 0; t < 6; t++)
#pragma unroll
        for (int j = 0; j < 2; j++) xv[t][j] = __ldg((const uint4*)(P.px + (t0 + t) * DM) + j * 32 + lane);
#pragma unroll
      for (int j = 0; j < 2; j++) { a[j] = __ldg(wr + j * 32 + lane); b[j] = __ldg(gw + j * 32 + lane); }
      for (int i = tid - 544; i < 512; i += 96) g_o[((tq * 4 + (i >> 7)) * 2 + 1) * 2048 + hp * 128 + (i & 127)] = make_uint4(0, 0, 0, 0);
#pragma unroll
      for (int t = 0; t < 6; t++) {
        float r = 0.f, g = 0.f;
#pragma unroll
        for (int j = 0; j < 2; j++) {
          const uint32_t xu[4] = {xv[t][j].x, xv[t][j].y, xv[t][j].z, xv[t][j].w};
          const uint32_t au[4] = {a[j].x, a[j].y, a[j].z, a[j].w}, bu[4] = {b[j].x, b[j].y, b[j].z, b[j].w};
#pragma unroll
          for (int i = 0; i < 4; i++) {
            r += b_lo(xu[i]) * b_lo(au[i]) + b_hi(xu[i]) * b_hi(au[i]);
            g += b_lo(xu[i]) * b_lo(bu[i]) + b_hi(xu[i]) * b_hi(bu[i]);
          }
        }
#pragma unroll
        for (int d = 16; d; d >>= 1) { r += __shfl_xor_sync(~0u, r, d); g += __shfl_xor_sync(~0u, g, d); }
        if (lane == 0 && (t < 5 || wi == 3)) { cell_set(g_r + t0 + t, __float_as_uint(r), epoch); cell_set(g_g + t0 + t, __float_as_uint(sigmoidf(g)), epoch); }
      }
    }
    asm volatile("setmaxnreg.dec.sync.aligned.u32 32;");
    if (wi >= 2) { bar_arrive(1, NTHR); return; }
    if (wi == 1) {
      bar_sync(1, NTHR);
      if (elect()) {
        bulk_out(g_kv + (hp * 32 + tq * 2) * 512, sb + 2 * SLOT, 2 * SLOT);
        asm volatile("cp.async.bulk.commit_group;" ::: "memory");
        const uint4 st = *(const uint4*)(sm + SM_STAT);
        asm volatile("cp.async.bulk.wait_group 0;" ::: "memory");
        fence_async_g();
        asm volatile("st.relaxed.gpu.global.v2.u32 [%0], {%1, %2};"
          ::"l"(g_f1 + hp * 8 + tq), "r"(min((st.x >> 16) + 1, 0x7fffu) | (st.y & 0xffff0000u)), "r"(epoch) : "memory");
        TSTAMP(4, true)
        mbar_wait(bars + B_KV * 8, 0);
        bulk_out(g_kv + (hp * 32 + 16 + tq * 2) * 512, sb, 2 * SLOT);
        asm volatile("cp.async.bulk.commit_group;" ::: "memory");
        asm volatile("cp.async.bulk.wait_group 0;" ::: "memory");
        fence_async_g();
        asm volatile("st.relaxed.gpu.global.v2.u32 [%0 + 8], {%1, %2};"
          ::"l"(g_f1 + hp * 8 + tq), "r"(min((st.z >> 16) + 1, 0x7fffu) | (st.w & 0xffff0000u)), "r"(epoch) : "memory");
      }
      return;
    }
    if (elect()) {
#pragma unroll 1
      for (int kc = NSTAGE; kc < 8; kc++) {
        const uint32_t st = sb + (kc - 3) * STG, bar = bars + (B_FULL + kc - NSTAGE) * 8;
        mbar_wait(bars + (B_EMPTY + kc - NSTAGE) * 8, 0);
        mbar_expect(bar, STG);
        tma3d(st + STG_A, &P.w, hp * 32, kc * 64, 0, bar);
        tma2d(st, &P.x, kc * 64, tq * 256, bar);
      }
      asm volatile("cp.async.bulk.prefetch.L2.global [%0], %1;" ::"l"(P.pwo + cta * 2048), "r"(4096) : "memory");
    }
    __syncwarp();
    bar_sync(1, NTHR);
    {
      const uint4* fp = g_f1 + hp * 8 + ((tq + lane) & 7);
      uint32_t sa, sc, rdy = 1, got = 1, c = 0;
#pragma unroll 1
      for (int pos = 2; pos < 16; pos++) {
        if (pos == 5) mbar_wait(bars + (B_KV + 1) * 8, 0);
        if (pos == 9) {
#pragma unroll
          for (int d = 1; d < 8; d <<= 1) { sa = __vmaxu2(sa, __shfl_xor_sync(~0u, sa, d)); sc = __vmaxu2(sc, __shfl_xor_sync(~0u, sc, d)); }
          if (lane == 0) { *(uint4*)(sm + SM_STAT + 16) = make_uint4(q_limit(sa), q_limit(sc), sa, sc); mbar_arrive(bars + (B_KV + 4) * 8); }
          mbar_wait(bars + B_FREE0 * 8, 0);
          got = 1;
        }
        if (pos == 13) mbar_wait(bars + B_FREE1 * 8, 0);
        if (pos == 8 || !(rdy & ~got)) {
          do {
            uint32_t e0, e1;
            asm volatile("ld.acquire.gpu.global.v4.u32 {%0, %1, %2, %3}, [%4];" : "=r"(sa), "=r"(e0), "=r"(sc), "=r"(e1) : "l"(fp) : "memory");
            rdy = __ballot_sync(~0u, e0 == epoch && (pos < 8 || e1 == epoch)) & 0xff;
          } while ((pos == 8 ? rdy != 0xff : !(rdy & ~got)) && ++c < SPIN_LIMIT);
          TSTAMP(6, lane == 0 && pos == 2)
          fence_async_g();
        }
        const int i = __ffs(rdy & ~got) - 1;
        got |= 1u << i;
        const uint32_t bar = bars + (B_KV + (pos < 3 ? 0 : pos < 5 ? 1 : pos < 9 ? 2 : pos < 13 ? 4 : 3)) * 8;
        if (elect()) {
          mbar_expect(bar, 2 * SLOT);
          bulk(sb + (pos < 9 ? pos : pos - 9) * 2 * SLOT, g_kv + (hp * 16 + (pos < 9 ? 0 : 8) + ((tq + i) & 7)) * 1024, 2 * SLOT, bar);
        }
        TSTAMP(5, lane == 0 && pos == 2)
      }
    }
    __syncwarp();
    const unsigned long long u0 = cell_ld(g_g + rt3 * 64 + lane), u1 = cell_ld(g_g + rt3 * 64 + 32 + lane);
    if (elect()) {
      mbar_expect(bars + B_X * 8, 16384);
      tma2d(sb + SM_X, &P.xr, cs * 128, rt3 * 64, bars + B_X * 8);
      tma2d(sb + SM_X + 8192, &P.xr, cs * 128 + 64, rt3 * 64, bars + B_X * 8);
      mbar_expect(bars + B_WO * 8, 98304);
#pragma unroll
      for (int j = 0; j < 3; j++) tma2d(sb + SM_WO + j * 32768, &P.wo, cs * 128 + (j ? 64 : 0), (j >> 1) * 256, bars + B_WO * 8);
    }
    __syncwarp();
#pragma unroll
    for (int i = 0; i < 2; i++) {
      const float g = __uint_as_float(cell_fin(g_g + rt3 * 64 + i * 32 + lane, i ? u1 : u0, epoch));
      *(uint2*)(sm + SM_G + i * 256 + lane * 8) = make_uint2(pack_b2(g, g), pack_b2(1.f - g, 1.f - g));
    }
    mbar_wait(bars + B_ORDY * 8, 0);
    if (lane == 0) asm volatile("st.release.gpu.global.u32 [%0], %1;" ::"l"(g_f2 + cta), "r"(epoch) : "memory");
    mbar_wait(bars + B_FREE2 * 8, 0);
    if (elect()) { mbar_expect(bars + B_WO * 8, 32768); tma2d(sb + SM_WO3, &P.wo, cs * 128, 256, bars + B_WO * 8); }
    __syncwarp();
    uint32_t v, c = 0;
    do {
      asm volatile("ld.acquire.gpu.global.u32 %0, [%1];" : "=r"(v) : "l"(g_f2 + tq * 16 + (lane & 15)) : "memory");
      if (++c > SPIN_LIMIT) break;
    } while (!__all_sync(~0u, v == epoch));
    if (elect()) {
      fence_async_g();
      mbar_expect(bars + B_OA * 8, 32768);
      bulk(sb + SM_OA, g_o + rt3 * 4096, 32768, bars + B_OA * 8);
    }
    __syncwarp();
    uint32_t idx, e;
    c = 0;
    do {
      asm volatile("ld.acquire.gpu.global.v2.u32 {%0, %1}, [%2];" : "=r"(idx), "=r"(e) : "l"(g_fy + (lane & 3)) : "memory");
      if (++c > SPIN_LIMIT) break;
    } while (!__all_sync(~0u, e == epoch));
    mbar_wait(bars + B_X * 8, 0);
#pragma unroll 1
    for (int t = 0; t < 2; t++) {
      const uint32_t d = ((idx >> (16 * t)) & 0xffff) - rt3 * 64;
      if (d < 64) {
        float4 y[NFFN];
#pragma unroll
        for (int f = 0; f < NFFN; f++) y[f] = __ldcg((const float4*)(g_y + (f * 2 + t) * DM + cs * 128) + lane);
        uint2* xp = (uint2*)(sm + SM_X + (lane >> 4) * 8192 + d * 128 + ((((lane >> 1) ^ d) & 7) << 4) + (lane & 1) * 8);
        const uint2 xv = *xp;
        *xp = make_uint2(pack_b2(b_lo(xv.x) + ((y[0].x + y[1].x) + (y[2].x + y[3].x)), b_hi(xv.x) + ((y[0].y + y[1].y) + (y[2].y + y[3].y))),
                         pack_b2(b_lo(xv.y) + ((y[0].z + y[1].z) + (y[2].z + y[3].z)), b_hi(xv.y) + ((y[0].w + y[1].w) + (y[2].w + y[3].w))));
      }
    }
    __syncwarp();
    if (lane == 0) { mbar_arrive(bars + B_Y * 8); g_epoch[cta] = epoch; }
    TSTAMP(15, lane == 0)
    return;
  }

  uint32_t q[4], q2[4], qn[2];
  {
    float acc[48];
#pragma unroll 1
    for (int kc = 0; kc < 8; kc++) {
      const int s = kc >= NSTAGE ? kc - NSTAGE : kc;
      const uint32_t st = sb + (kc < 3 ? kc + 2 : kc - 3) * STG;
      mbar_wait(bars + (B_FULL + s) * 8, kc >= NSTAGE);
      TSTAMP(1, tid == 0 && kc == 0)
      TSTAMPD(13, 8 + kc, tid == 0)
      const uint64_t da = make_desc(st + (wg ^ cs) * 8192, 16, 1024, 1), db = make_desc(st + STG_A, 4096, 512, 2);
      wg_fence();
#pragma unroll
      for (int ks = 0; ks < 4; ks++) wg_ss_n96(acc, da + ks * 2, db + ks * 64, kc | ks);
      wg_commit();
      wg_wait<1>();
      if (kc >= 1 && kc <= 4 && lane == 0) mbar_arrive(bars + (B_EMPTY + kc - 1) * 8);
    }
    mbar_wait(bars + (B_EMPTY + 3) * 8, 0);
    wg_wait<0>();
    pin<48>(acc);
    asm volatile("setmaxnreg.inc.sync.aligned.u32 112;");
    TSTAMP(2, tid == 0)
    const uint32_t ka = sb + (wg >> 1) * SLOT + (warp & 7) * 512 + (lane & 15) * 32 + (((lane >> 4) ^ (lane >> 2)) & 1) * 16;
#pragma unroll
    for (int hb = 1; hb >= 0; hb--) {
      uint32_t kk[4], vv[4];
#pragma unroll
      for (int i = 0; i < 4; i++) {
        kk[i] = pack_h2(acc[16 + hb * 8 + 2 * i], acc[17 + hb * 8 + 2 * i]);
        vv[i] = pack_h2(acc[32 + hb * 8 + 2 * i], acc[33 + hb * 8 + 2 * i]);
      }
      stsm4(ka + (1 - hb) * 2 * SLOT, kk);
      stsm4(ka + (1 - hb) * 2 * SLOT + 4096, vv);
    }
    fence_async();
#pragma unroll
    for (int hb = 0; hb < 2; hb++) {
      const float* v = acc + 32 + hb * 8;
      uint32_t vm = 0;
#pragma unroll
      for (int i = 0; i < 8; i++) vm = max(vm, __float_as_uint(v[i]) & 0x7fffffffu);
      vm = __reduce_max_sync(~0u, vm);
      const uint32_t kn = max_norm2(acc + 16 + hb * 8);
      if (lane < 2) atomicMax((uint32_t*)(sm + SM_STAT + hb * 8 + lane * 4), lane ? vm : kn);
      qn[hb] = max_norm2(acc + hb * 8);
    }
#pragma unroll
    for (int i = 0; i < 4; i++) { q2[i] = pack_h2(acc[2 * i] * QS, acc[2 * i + 1] * QS); q[i] = pack_h2(acc[8 + 2 * i] * QS, acc[9 + 2 * i] * QS); }
  }
  bar_sync(1, NTHR);
  TSTAMP(3, tid == 0)

  uint32_t* const op = (uint32_t*)g_o + __reduce_max_sync(~0u, (uint32_t)(((tq * 4 + (wg ^ cs)) * 4096 + hp * 128 + wi * 32) * 4));
  uint32_t redo = 0;
  const uint32_t park = sb + SM_PARK + tid * 16;
  sts128(park, q2); sts128(park + 8192, q);
  {
    uint32_t cb, cm, ce, c16;
    asm volatile("ld.volatile.shared.v4.u32 {%0, %1, %2, %3}, [%4];" : "=r"(cb), "=r"(cm), "=r"(ce), "=r"(c16) : "r"(sb + SM_STAT + 32));
    uint64_t dk = kv_desc(sb);
    uint32_t bs, ba;
    asm volatile("ld.volatile.shared.v2.u32 {%0, %1}, [%2];" : "=r"(bs), "=r"(ba) : "r"(sb + SM_STAT + 48 + wg * 8));
    uint32_t tab = sb + SM_TAB + wg * 64, src = sb + SM_STAT + 80, ss = 0;
    uint32_t s[32], p[32], o[12];
    wg_fence(); wg_qk(s, q, dk); wg_commit();
    if (wg == 3) bar_arrive(4, 256);
#pragma unroll 1
    for (int ph = 0;; ph++) {
      lds128(o, src); lds64(o + 4, src + 2 * ss); lds128(o + 6, src + ss); lds64(o + 10, src + 2 * ss + 8);
      __syncwarp();
      if (ss && lane == 0) mbar_arrive(bars + B_FREE1 * 8);
      pin<12>(o);
      wg_wait<0>();
      pin<32>(s);
      TSTAMPD(14, 13 + ph, tid == 0)
#pragma unroll 1
      for (;;) {
        uint32_t ex[2];
        lds64(ex, tab);
        tab += 8;
#pragma unroll 1
        do {
          desc_step(dk, (int)VT);
          exp2_tile(s, p, cb, cm, ce, c16);
          wg_fence();
          wg_pv(o, p, dk - 8 * VK);
          bar_sync(bs, 256);
#pragma unroll
          for (int j = 1; j < 8; j++) wg_pv(o + (j & 1) * 6, p + j * 4, dk - (8 - j) * VK);
          wg_qk(s, q, dk + QKO);
          wg_commit();
          bar_arrive(ba, 256);
          wg_wait<0>();
          pin<32>(s);
        } while ((uint32_t)dk != ex[0]);
        if (!ex[1]) break;
        TSTAMPD(11, 16 + (tab >> 2 & 14), tid == 0)
        mbar_wait(ex[1], wg & 1);
        TSTAMPD(11, 17 + (tab >> 2 & 14), tid == 0)
        asm volatile("{.reg .pred p; setp.eq.u32 p, %1, 256; @p mbarrier.arrive.shared::cta.b64 _, [%0];}" ::"r"(ex[1]), "r"(tid & 0x11f) : "memory");
        __syncwarp();
      }
      pin<12>(o);
      const int hb = ph >> 1;
      TSTAMPD(12, tid ? 16 : 10 + ph, tid == 0 || tid == 384)
      if (!hb) {
        lds128(q, park + ph * 8192);
        desc_step(dk, ph * (int)(-NSLOT * VT));
        if (ph) mbar_wait(bars + (B_KV + 4) * 8, 0);
        wg_fence(); wg_qk(s, q, dk); wg_commit();
      }
      if (ph == 0) {
        sts128(park + 16384, o); sts128(park + 24576, o + 6); sts64(park + 32768, o + 4); sts64(park + 32776, o + 10);
        continue;
      }
      uint32_t lim;
      asm volatile("ld.shared.u32 %0, [%1];" : "=r"(lim) : "r"(sb + SM_STAT + 12 + ph * 4));
      uint32_t l2, ok;
#pragma unroll
      for (int i = 0; i < 6; i++) asm("add.f16x2 %0, %0, %1;" : "+r"(o[i]) : "r"(o[6 + i]));
      float i0, i1;
      asm("rcp.approx.ftz.f32 %0, %1;" : "=f"(i0) : "f"(h_lo(o[4])));
      asm("rcp.approx.ftz.f32 %0, %1;" : "=f"(i1) : "f"(h_lo(o[5])));
      l2 = __byte_perm(o[4], o[5], 0x5410);
#pragma unroll
      for (int i = 0; i < 4; i++) asm("fma.rn.f16x2 %0, %1, %2, %0;" : "+r"(l2) : "r"(o[i]), "r"(0));
      asm("{.reg .pred a, b, c, d; setp.ge.f16x2 a|b, %1, %2; setp.le.and.f16x2 c|d, %1, %3, a; and.pred c, c, d; and.pred c, c, b; selp.u32 %0, 1, 0, c;}"
        : "=r"(ok) : "r"(l2), "r"(0x54005400), "r"(0x7bff7bff));
      if (__all_sync(~0u, ok && (hb ? qn[1] : qn[0]) < lim)) {
#pragma unroll
        for (int i = 0; i < 4; i++) o[i] = pack_b2(h_lo(o[i]) * ((i & 1) ? i1 : i0), h_hi(o[i]) * ((i & 1) ? i1 : i0));
        if (hb) {
          asm volatile("st.relaxed.gpu.global.v4.u32 [%0], {%1, %2, %3, %4};" ::"l"(op + 8192 + lane * 4), "r"(max(o[0], 1u)), "r"(max(o[1], 1u)), "r"(max(o[2], 1u)), "r"(max(o[3], 1u)) : "memory");
          break;
        }
#pragma unroll
        for (int i = 0; i < 4; i++) o_store(op, 0, lane, i, o[i]);
        __syncwarp();
        if (lane == 0) mbar_arrive(bars + B_ORDY * 8);
      } else {
        redo |= 1 << hb;
        if (!hb) { lds128(o, park); ((uint4*)op)[lane] = make_uint4(o[0], o[1], o[2], o[3]); }
      }
      if (hb) break;
      src = park + 16384; ss = 8192;
    }
    wg_wait<0>();
  }
  TSTAMP(17, tid == 384)
  if (redo) {
#pragma unroll 1
    for (int hb = 0; hb < 2; hb++) {
      const bool in_range = kv_in_range(*(const uint32_t*)(sm + SM_STAT + 24 + hb * 4)) && __uint_as_float(hb ? qn[1] : qn[0]) * (QS * QS) <= 1.6e7f;
      const uint32_t m = (redo >> hb & 1) ? (in_range ? 1 : 3) : 0;
      if (m == 1) {
        const uint4 t = hb ? make_uint4(q[0], q[1], q[2], q[3]) : ((const uint4*)op)[lane];
        attn_true_max(t.x, t.y, t.z, t.w, hp * 2 + hb, op + hb * 8192);
      }
      if (m == 3) attn_fp32(P.px, P.pw, hp * 2 + hb, tq * 256 + (warp ^ cs * 4) * 16, op + hb * 8192);
      __syncwarp();
      if (m && !hb && lane == 0) mbar_arrive(bars + B_ORDY * 8);
    }
  }

  const uint64_t db0 = make_desc(sb + SM_WO, 32768, 1024, 1), db1 = make_desc(sb + SM_WO3, SM_WO + 65536 - SM_WO3, 1024, 1);
  if (wg == 1) {
    asm volatile("setmaxnreg.dec.sync.aligned.u32 32;");
  } else if (wg == 0) {
    int tid;
    asm volatile("mov.u32 %0, %tid.x;" : "=r"(tid));
    const int lane = tid & 31, wi = tid >> 5;
    float acc[64];
    uint32_t pre[32];
    const uint32_t stg = sb + SM_X + wi * 2048;
    const uint32_t fr = stg + (lane & 15) * 128 + (((lane >> 4) ^ lane) & 7) * 16;
    mbar_wait(bars + B_WO * 8, 0);
    mbar_wait(bars + B_OA * 8, 0);
    asm volatile("setmaxnreg.inc.sync.aligned.u32 192;");
    uint32_t a[64];
    const uint4* src[4];
    const uint32_t rx = __reduce_max_sync(~0u, (uint32_t)(rt3 & 3) * 256 + 128);
    const uint64_t dc0 = (db0 >> 32 << 32) + __reduce_max_sync(~0u, (uint32_t)db0), dc1 = (db1 >> 32 << 32) + __reduce_max_sync(~0u, (uint32_t)db1);
#pragma unroll
    for (int j = 0; j < 4; j++) src[j] = g_o + rt3 * 4096 + 2048 + ((rt3 ^ j) & 3) * 128 + tid;
#pragma unroll
    for (int k = 0; k < 16; k++)
      if ((LDAT >> (k >> 2) * 8 & 31) == 0) o_load(a + k * 4, src[k >> 2] + (k & 3) * 512);
    bar_sync(4, 256);
#pragma unroll
    for (int ks = 0; ks < 16; ks++) {
      if (ks == 0 || (LDAT >> 0 & 31) == ks || (LDAT >> 8 & 31) == ks || (LDAT >> 16 & 31) == ks || (LDAT >> 24 & 31) == ks) wg_fence();
      wg_ss_n128(acc, make_desc(sb + SM_OA, 128, 256, 0) + ks * 128, (ks < 8 ? db0 : db1) + (ks & 7) * 256, ks);
      if (ks == 15) wg_commit();
#pragma unroll
      for (int j = 0; j < 4; j++)
        if ((LDAT >> j * 8 & 31) == ks + 1) {
          if (j == 0 || (LDAT >> (j * 8 - 8) & 31) != ks + 1) bar_sync(8, 128);
#pragma unroll
          for (int m = 0; m < 4; m++) o_load(a + j * 16 + m * 4, src[j] + m * 512);
          if (j == 3 || (LDAT >> (j * 8 + 8) & 31) != ks + 1) bar_sync(8, 128);
        }
    }
    TSTAMP(26, tid == 0)
    uint4* dst = (uint4*)(P.pout + (rt3 * 64 + wi * 16 + (lane >> 3)) * DM + cs * 128) + (lane & 7);
    uint32_t rd = stg + (lane >> 3) * 128 + ((lane ^ lane >> 3) & 7) * 16;
    asm volatile("" : "+l"(dst), "+r"(rd));
    uint32_t g[4];
#pragma unroll
    for (int j = 0; j < 4; j++) {
      uint32_t nz = ~0u;
      if (j == 0) asm volatile("ld.volatile.shared.u32 %0, [%1];" : "=r"(nz) : "r"(sb + SM_ONE) : "memory");
      if (missing(a + j * 16, nz)) {
        uint32_t c = 0;
#pragma unroll 1
        do {
#pragma unroll
          for (int k = j * 4; k < 16; k++) o_reload(a + k * 4, src[k >> 2] + (k & 3) * 512);
        } while (missing(a + j * 16) && ++c < SPIN_LIMIT);
      }
      TSTAMP(18 + j * 2, tid == 0)
      wg_fence();
#pragma unroll
      for (int m = 0; m < 4; m++) wg_rs_n128(acc, a + j * 16 + m * 4, (m < 2 ? dc0 : dc1) + (m & 1) * 1024 + (rx ^ j * 256));
      wg_commit();
      if (j == 3) {
        mbar_wait(bars + B_Y * 8, 0);
        lds64(g, sb + SM_G + (wi * 16 + (lane >> 2)) * 8); lds64(g + 2, sb + SM_G + (wi * 16 + 8 + (lane >> 2)) * 8);
#pragma unroll
        for (int j = 0; j < 8; j++) ldsm4(pre + j * 4, (fr ^ (j & 3) * 32) + (j >> 2) * 8192);
#pragma unroll
        for (int i = 0; i < 32; i++) asm("mul.rn.bf16x2 %0, %0, %1;" : "+r"(pre[i]) : "r"(g[(i & 1) * 2 + 1]));
        pin<32>(pre);
        mbar_wait(bars + B_Y * 8, 0);
      }
    }
    wg_wait<0>();
    pin<64>(acc);
    TSTAMP(9, tid == 0)
#pragma unroll
    for (int h = 0; h < 2; h++) {
#pragma unroll
      for (int j = h * 4; j < h * 4 + 4; j++) {
#pragma unroll
        for (int i = j * 4; i < j * 4 + 4; i++) asm("fma.rn.bf16x2 %0, %1, %2, %0;" : "+r"(pre[i]) : "r"(pack_b2(acc[2 * i], acc[2 * i + 1])), "r"(g[(i & 1) * 2]));
        stsm4((fr ^ (j & 3) * 32) + h * 8192, pre + j * 4);
      }
      __syncwarp();
#pragma unroll
      for (int j = 0; j < 4; j++) lds128(a + h * 16 + j * 4, (rd ^ (j & 1) * 64) + j * 512 + h * 8192);
#pragma unroll
      for (int k = h * 4; k < h * 4 + 4; k++)
        asm volatile("st.global.v4.u32 [%0], {%1, %2, %3, %4};" ::"l"(dst + (k & 3) * 4 * DM / 8 + h * 8), "r"(a[k * 4]), "r"(a[k * 4 + 1]), "r"(a[k * 4 + 2]), "r"(a[k * 4 + 3]) : "memory");
    }
    TSTAMP(7, tid == 0)
  }
}

typedef CUresult (*EncodeFn)(CUtensorMap*, CUtensorMapDataType, cuuint32_t, void*, const cuuint64_t*, const cuuint64_t*,
                             const cuuint32_t*, const cuuint32_t*, CUtensorMapInterleave, CUtensorMapSwizzle,
                             CUtensorMapL2promotion, CUtensorMapFloatOOBfill);
static void make_map(EncodeFn enc, CUtensorMap* m, const void* p, int cols, int rows, int box_rows) {
  cuuint64_t dim[2] = {(cuuint64_t)cols, (cuuint64_t)rows}, str[1] = {(cuuint64_t)cols * 2};
  cuuint32_t box[2] = {64, (cuuint32_t)box_rows}, es[2] = {1, 1};
  enc(m, CU_TENSOR_MAP_DATA_TYPE_BFLOAT16, 2, (void*)p, dim, str, box, es, CU_TENSOR_MAP_INTERLEAVE_NONE,
      CU_TENSOR_MAP_SWIZZLE_128B, CU_TENSOR_MAP_L2_PROMOTION_L2_128B, CU_TENSOR_MAP_FLOAT_OOB_FILL_NONE);
}

extern "C" void kernel_launch(void* const* d_in, const int* in_sizes, int n_in, void* d_out, int out_size) {
  static EncodeFn enc = nullptr;
  if (!enc) {
    void* fn = nullptr; cudaDriverEntryPointQueryResult qr;
    cudaGetDriverEntryPoint("cuTensorMapEncodeTiled", &fn, cudaEnableDefault, &qr);
    enc = (EncodeFn)fn;
    cudaFuncSetAttribute(fused_kernel, cudaFuncAttributeMaxDynamicSharedMemorySize, SM_TOTAL);
  }
  Params P;
  make_map(enc, &P.x, d_in[0], DM, SEQ, 256);
  make_map(enc, &P.wo, d_in[2], DM, DM, 256);
  make_map(enc, &P.xr, d_in[0], DM, SEQ, 64);
  make_map(enc, &P.wg, d_in[5], FF, DM, 256);
  make_map(enc, &P.wu, d_in[6], FF, DM, 256);
  make_map(enc, &P.wd, d_in[7], DM, FF, 224);
  {
    cuuint64_t dim[3] = {DM, DM, 3}, str[2] = {3 * DM * 2, DM * 2};
    cuuint32_t box[3] = {32, 64, 3}, es[3] = {1, 1, 1};
    enc(&P.w, CU_TENSOR_MAP_DATA_TYPE_BFLOAT16, 3, d_in[1], dim, str, box, es, CU_TENSOR_MAP_INTERLEAVE_NONE,
        CU_TENSOR_MAP_SWIZZLE_64B, CU_TENSOR_MAP_L2_PROMOTION_L2_128B, CU_TENSOR_MAP_FLOAT_OOB_FILL_NONE);
  }
  P.px = (const bf16*)d_in[0]; P.pw = (const bf16*)d_in[1]; P.pwo = (const bf16*)d_in[2];
  P.pout = (bf16*)d_out;
  P.pwr = (const bf16*)d_in[4]; P.pgw = (const bf16*)d_in[8];
  fused_kernel<<<NCTA, NTHR, SM_TOTAL, cudaStreamPerThread>>>(P);
}
```
